```python
import torch

def _softmax(x, axis=-1):
    return torch.softmax(x, dim=axis)
def _gelu(x):
    return torch.nn.functional.gelu(x, approximate="tanh")
def _silu(x):
    return torch.nn.functional.silu(x)
def _sigmoid(x):
    return torch.sigmoid(x)
def _layernorm(x, axis=-1, eps=1e-5):
    m = x.mean(dim=axis, keepdim=True)
    v = x.var(dim=axis, keepdim=True, unbiased=False)
    return (x - m) / torch.sqrt(v + eps)
def _scatter_add(tgt, idx, src, axis=0):
    return tgt.clone().index_add_(axis, idx, src)
def _segment_sum(src, seg, n):
    out = torch.zeros((n,) + src.shape[1:], dtype=src.dtype)
    return out.index_add_(0, seg, src)
def _pad(x, pw):
    flat = tuple(v for pair in reversed(pw) for v in pair)
    return torch.nn.functional.pad(x, flat)

kernel_name = 'recurrent_scan__sliding_local_dilated__swiglu_ffn__prompt'

def setup_inputs():

    _w = (lambda a: (lambda t: t.to(torch.bfloat16) if t.is_floating_point() else t)(torch.as_tensor(a)))
    def _A_setup():
        B, S, D = 1, 2048, 448
        return {
            "x": _w((lambda *s: torch.randn(*s, dtype=torch.bfloat16) * 0.05)(B, S, D)),
            "wqkv": _w((lambda *s: torch.randn(*s, dtype=torch.bfloat16) * 0.05)(D, 3 * D)),
            "wo": _w((lambda *s: torch.randn(*s, dtype=torch.bfloat16) * 0.05)(D, D)),
        }
    _A_in = _A_setup()

    def _B_setup():
        B, S, D, F = 1, 2048, 448, 1792
        return {
            "x": _w((lambda *s: torch.randn(*s, dtype=torch.bfloat16) * 0.05)(B, S, D)),
            "w_gate": _w((lambda *s: torch.randn(*s, dtype=torch.bfloat16) * 0.05)(D, F)),
            "w_up": _w((lambda *s: torch.randn(*s, dtype=torch.bfloat16) * 0.05)(D, F)),
            "w_down": _w((lambda *s: torch.randn(*s, dtype=torch.bfloat16) * 0.05)(F, D)),
        }
    _B_in = _B_setup()

    return {
        "A_x": _A_in["x"],
        "A_wqkv": _A_in["wqkv"],
        "A_wo": _A_in["wo"],
        "B_x": _B_in["x"],
        "B_w_gate": _B_in["w_gate"],
        "B_w_up": _B_in["w_up"],
        "B_w_down": _B_in["w_down"],
    }

def reference(A_x, A_wqkv, A_wo, B_x, B_w_gate, B_w_up, B_w_down):
    def _A_ref(x, wqkv, wo):
        B, S, D = x.shape
        H = 16; Dh = D // H
        W, dil = 8, 2
        qkv = (lambda x, *d: x.permute(*d))((x @ wqkv).reshape(B, S, 3, H, Dh), 2, 0, 3, 1, 4)
        q, k, v = qkv[0], qkv[1], qkv[2]
        scale = Dh ** -0.5
        pos = torch.arange(S)
        off = torch.arange(W) * dil
        idx = pos[:, None] - off[None, :]
        mask = idx >= 0
        idx_c = torch.where(mask, idx, 0).reshape(-1)
        kg = k[:, :, idx_c, :].reshape(B, H, S, W, Dh)
        vg = v[:, :, idx_c, :].reshape(B, H, S, W, Dh)
        logits = torch.einsum("bhsd,bhswd->bhsw", q, kg) * scale
        logits = torch.where(mask[None, None, :, :], logits, -1e9)
        attn = _softmax(logits, axis=-1)
        o = torch.einsum("bhsw,bhswd->bhsd", attn, vg)
        return (lambda x, *d: x.permute(*d))(o, 0, 2, 1, 3).reshape(B, S, D) @ wo

    def _B_ref(x, w_gate, w_up, w_down):
        g = _silu(x @ w_gate)
        u = x @ w_up
        return (g * u) @ w_down

    x = A_x
    xn = _layernorm(x, axis=-1)
    s = _A_ref(xn, A_wqkv, A_wo)
    g = _silu(_B_ref(xn, B_w_gate, B_w_up, B_w_down))
    return x + s * g
```

```cpp
#include <cuda_runtime.h>
#include <cuda.h>
#include <cuda_bf16.h>
#include <stdint.h>

namespace {

constexpr uint32_t SLOT = 28672;
constexpr uint32_t XR = 4 * SLOT;
constexpr uint32_t XH = 57344;
constexpr uint32_t MISC = 8 * SLOT;
constexpr uint32_t O_XFULL = MISC, O_FULL = MISC + 64, O_RECV = MISC + 336;
constexpr uint32_t O_EPOCH = MISC + 400, O_TAB = MISC + 352, O_RSTD = MISC + 1024;
constexpr uint32_t SLOT2 = 20480;
constexpr uint32_t SMEM_BYTES = MISC + 3072;
#define ISS 4
#define NAP 30
#define FB 6
#define PH 0xa00
#define PB 0x784
#define TWO 0
#define EM 0
#define ZL 2
#define ZG 2
#define EP 2
constexpr int SPIN_MAX = 1 << 16;

struct Maps { CUtensorMap m[12]; };

constexpr uint32_t FST = 1088, SROWS = 1056;
constexpr uint32_t G_S = 132 * FST / 4, G_E = G_S + 32 * SROWS * 16;
__device__ uint4 g_part[G_E + 6 * SROWS * 8];
#define PT3(i) do {} while (0)
#define RT(f) do {} while (0)
#define PT4(i) do {} while (0)
#define PT2(i) do {} while (0)
#define PT(i) do {} while (0)
#define GT(i) do {} while (0)
#define PT0A() do {} while (0)
#define PT0B() do {} while (0)
#define PDUMP() do {} while (0)

__device__ __forceinline__ void mbar_init(uint32_t bar, uint32_t cnt) { asm volatile("mbarrier.init.shared::cta.b64 [%0], %1;" :: "r"(bar), "r"(cnt) : "memory"); }
__device__ __forceinline__ void mbar_expect_tx(uint32_t bar, uint32_t bytes) { asm volatile("mbarrier.arrive.expect_tx.shared::cta.b64 _, [%0], %1;" :: "r"(bar), "r"(bytes) : "memory"); }
__device__ __forceinline__ void mbar_wait(uint32_t bar, uint32_t parity) {
    asm volatile("{ .reg .pred p; .reg .s32 n; mov.s32 n, 1048576;\n"
        "W: mbarrier.try_wait.parity.shared::cta.b64 p, [%0], %1; add.s32 n, n, -1; setp.gt.and.s32 p, n, 0, !p; @p bra W; }"
        :: "r"(bar), "r"(parity) : "memory");
}
__device__ __forceinline__ uint32_t mapa(uint32_t a, uint32_t cta) { uint32_t r; asm volatile("mapa.shared::cluster.u32 %0, %1, %2;" : "=r"(r) : "r"(a), "r"(cta)); return r; }
__device__ __forceinline__ void tma3d(uint32_t dst, const void* m, int blk, int row, uint32_t bar, int col = 0) {
    asm volatile("cp.async.bulk.tensor.3d.shared::cluster.global.mbarrier::complete_tx::bytes [%0], [%1, {%5, %4, %3}], [%2];"
        :: "r"(dst), "l"(m), "r"(bar), "r"(blk), "r"(row), "r"(col) : "memory"); }
__device__ __forceinline__ void tma3d_pf(const void* m, int blk, int row) {
    asm volatile("cp.async.bulk.prefetch.tensor.3d.L2.global [%0, {%3, %2, %1}];" :: "l"(m), "r"(blk), "r"(row), "r"(0) : "memory"); }
__device__ __forceinline__ void tma4d(uint32_t dst, const void* m, int c1, int c2, int c3, uint32_t bar) {
    asm volatile("cp.async.bulk.tensor.4d.shared::cluster.global.mbarrier::complete_tx::bytes [%0], [%1, {%6, %3, %4, %5}], [%2];"
        :: "r"(dst), "l"(m), "r"(bar), "r"(c1), "r"(c2), "r"(c3), "r"(0) : "memory"); }
__device__ __forceinline__ void bulk_ld(uint32_t dst, const void* src, uint32_t bytes, uint32_t bar) {
    asm volatile("cp.async.bulk.shared::cluster.global.mbarrier::complete_tx::bytes [%0], [%1], %2, [%3];" :: "r"(dst), "l"(src), "r"(bytes), "r"(bar) : "memory"); }
__device__ __forceinline__ void bulk_st(void* dst, uint32_t src, uint32_t bytes) {
    asm volatile("cp.async.bulk.global.shared::cta.bulk_group [%0], [%1], %2;" :: "l"(dst), "r"(src), "r"(bytes) : "memory"); }
__device__ __forceinline__ void bulk_commit() { asm volatile("cp.async.bulk.commit_group;" ::: "memory"); }
template<int N> __device__ __forceinline__ void bulk_wait() { asm volatile("cp.async.bulk.wait_group.read %0;" :: "n"(N) : "memory"); }
__device__ __forceinline__ void fence_async() { asm volatile("fence.proxy.async.shared::cta;" ::: "memory"); }
__device__ __forceinline__ bool elect_one() { uint32_t p; asm volatile("{ .reg .pred p; elect.sync _|p, 0xffffffff; selp.u32 %0, 1, 0, p; }" : "=r"(p)); return p; }
__device__ __forceinline__ void wg_fence() { asm volatile("wgmma.fence.sync.aligned;" ::: "memory"); }
__device__ __forceinline__ void wg_commit() { asm volatile("wgmma.commit_group.sync.aligned;" ::: "memory"); }
template<int N> __device__ __forceinline__ void wg_wait() { asm volatile("wgmma.wait_group.sync.aligned %0;" :: "n"(N) : "memory"); }
template<int O, int N, int SZ> __device__ __forceinline__ void pin(float (&d)[SZ]) {
    #pragma unroll
    for (int i = 0; i < N; i++) asm volatile("" : "+f"(d[O + i]) :: "memory");
}
__device__ __forceinline__ void ldsm4(uint32_t& a, uint32_t& b, uint32_t& c, uint32_t& d, uint32_t addr) {
    asm volatile("ldmatrix.sync.aligned.m8n8.x4.shared.b16 {%0,%1,%2,%3}, [%4];" : "=r"(a), "=r"(b), "=r"(c), "=r"(d) : "r"(addr) : "memory"); }
__device__ __forceinline__ void stsm4(uint32_t addr, uint32_t a, uint32_t b, uint32_t c, uint32_t d) {
    asm volatile("stmatrix.sync.aligned.m8n8.x4.shared.b16 [%0], {%1,%2,%3,%4};" :: "r"(addr), "r"(a), "r"(b), "r"(c), "r"(d) : "memory"); }
__device__ __forceinline__ void stsm2(uint32_t addr, uint32_t a, uint32_t b) {
    asm volatile("stmatrix.sync.aligned.m8n8.x2.shared.b16 [%0], {%1,%2};" :: "r"(addr), "r"(a), "r"(b) : "memory"); }
__device__ __forceinline__ void sts128(uint32_t addr, uint32_t a, uint32_t b, uint32_t c, uint32_t d) {
    asm volatile("st.shared.v4.u32 [%0], {%1,%2,%3,%4};" :: "r"(addr), "r"(a), "r"(b), "r"(c), "r"(d) : "memory"); }
__device__ __forceinline__ void lds128(uint32_t& a, uint32_t& b, uint32_t& c, uint32_t& d, uint32_t addr) {
    asm volatile("ld.shared.v4.u32 {%0,%1,%2,%3}, [%4];" : "=r"(a), "=r"(b), "=r"(c), "=r"(d) : "r"(addr) : "memory"); }
__device__ __forceinline__ void st_async4(uint32_t raddr, uint32_t a, uint32_t b, uint32_t c, uint32_t d, uint32_t rbar) {
    asm volatile("st.async.shared::cluster.mbarrier::complete_tx::bytes.v4.b32 [%0], {%1,%2,%3,%4}, [%5];" :: "r"(raddr), "r"(a), "r"(b), "r"(c), "r"(d), "r"(rbar) : "memory"); }
__device__ __forceinline__ uint32_t ld_flag(const uint32_t* p) { uint32_t v; asm volatile("ld.relaxed.gpu.global.u32 %0, [%1];" : "=r"(v) : "l"(p) : "memory"); return v; }
template<int N> __device__ __forceinline__ void publish(uint32_t* p, uint32_t v, uint32_t lane) {
    bulk_wait<N>();
    __syncwarp();
    if (lane == 0) asm volatile("st.relaxed.gpu.global.u32 [%0], %1;" :: "l"(p), "r"(v) : "memory");
}
__device__ __forceinline__ void gate(const uint32_t* p, uint32_t& v, uint32_t need, bool act) {
    #pragma unroll 1
    for (int k = 0; k < SPIN_MAX && !__all_sync(0xffffffffu, (int)(v - need) >= 0); k++) { if (k) __nanosleep(100); if (act) v = ld_flag(p); }
}
__device__ __forceinline__ uint32_t pack2(float lo, float hi) { uint32_t r; asm("cvt.rn.bf16x2.f32 %0, %1, %2;" : "=r"(r) : "f"(hi), "f"(lo)); return r; }
__device__ __forceinline__ uint32_t hmul2(uint32_t a, uint32_t b) { uint32_t r; asm("mul.rn.bf16x2 %0, %1, %2;" : "=r"(r) : "r"(a), "r"(b)); return r; }
__device__ __forceinline__ uint32_t hfma2(uint32_t a, uint32_t b, uint32_t c) { uint32_t r; asm("fma.rn.bf16x2 %0, %1, %2, %3;" : "=r"(r) : "r"(a), "r"(b), "r"(c)); return r; }
__device__ __forceinline__ uint32_t hadd2(uint32_t a, uint32_t b) { uint32_t r; asm("add.rn.bf16x2 %0, %1, %2;" : "=r"(r) : "r"(a), "r"(b)); return r; }
__device__ __forceinline__ uint32_t hsub2(uint32_t a, uint32_t b) { uint32_t r; asm("sub.rn.bf16x2 %0, %1, %2;" : "=r"(r) : "r"(a), "r"(b)); return r; }
__device__ __forceinline__ void chk(uint32_t& bad, uint32_t v, uint32_t par) { asm("lop3.b32 %0, %0, %1, %2, 0xf6;" : "+r"(bad) : "r"(v), "r"(par)); }
__device__ __forceinline__ float bf_lo(uint32_t w) { return __uint_as_float(w << 16); }
__device__ __forceinline__ float bf_hi(uint32_t w) { return __uint_as_float(w & 0xffff0000u); }
__device__ __forceinline__ float bf_round(float x) { return bf_lo(pack2(x, 0.f)); }
__device__ __forceinline__ float tanh_fast(float x) { float r; asm("tanh.approx.f32 %0, %1;" : "=f"(r) : "f"(x)); return r; }
__device__ __forceinline__ float ex2(float x) { float r; asm("ex2.approx.ftz.f32 %0, %1;" : "=f"(r) : "f"(x)); return r; }
__device__ __forceinline__ float rcp(float x) { float r; asm("rcp.approx.ftz.f32 %0, %1;" : "=f"(r) : "f"(x)); return r; }
__device__ __forceinline__ float sqrt_fast(float x) { float r; asm("sqrt.approx.ftz.f32 %0, %1;" : "=f"(r) : "f"(x)); return r; }
__device__ __forceinline__ void hmma(float (&c)[4], uint32_t a0, uint32_t a1, uint32_t a2, uint32_t a3, uint32_t b0, uint32_t b1) {
    asm volatile("mma.sync.aligned.m16n8k16.row.col.f32.bf16.bf16.f32 {%0,%1,%2,%3}, {%4,%5,%6,%7}, {%8,%9}, {%0,%1,%2,%3};"
        : "+f"(c[0]), "+f"(c[1]), "+f"(c[2]), "+f"(c[3]) : "r"(a0), "r"(a1), "r"(a2), "r"(a3), "r"(b0), "r"(b1)); }

template<int O, int TB, int INC, int SZ> __device__ __forceinline__ void wg_a32(float (&d)[SZ], uint32_t a0, uint32_t a1, uint32_t a2, uint32_t a3, uint64_t& dd) {
    asm volatile("{ .reg .pred p; setp.ne.b32 p, 1, 0;"
        "wgmma.mma_async.sync.aligned.m64n32k16.f32.bf16.bf16 {%0, %1, %2, %3, %4, %5, %6, %7, %8, %9, %10, %11, %12, %13, %14, %15}, "
        "{%17, %18, %19, %20}, %16, p, 1, 1, %21; add.s64 %16, %16, %22; }"
        : "+f"(d[O + 0]), "+f"(d[O + 1]), "+f"(d[O + 2]), "+f"(d[O + 3]), "+f"(d[O + 4]), "+f"(d[O + 5]), "+f"(d[O + 6]), "+f"(d[O + 7]), "+f"(d[O + 8]), "+f"(d[O + 9]), "+f"(d[O + 10]), "+f"(d[O + 11]), "+f"(d[O + 12]), "+f"(d[O + 13]), "+f"(d[O + 14]), "+f"(d[O + 15]), "+l"(dd)
        : "r"(a0), "r"(a1), "r"(a2), "r"(a3), "n"(TB), "n"(INC));
}
template<int O, int TB, int INC, int SZ> __device__ __forceinline__ void wg_z32(float (&d)[SZ], uint32_t a0, uint32_t a1, uint32_t a2, uint32_t a3, uint64_t& dd) {
    asm volatile("{ .reg .pred p; setp.ne.b32 p, 0, 0;"
        "wgmma.mma_async.sync.aligned.m64n32k16.f32.bf16.bf16 {%0, %1, %2, %3, %4, %5, %6, %7, %8, %9, %10, %11, %12, %13, %14, %15}, "
        "{%17, %18, %19, %20}, %16, p, 1, 1, %21; add.s64 %16, %16, %22; }"
        : "=f"(d[O + 0]), "=f"(d[O + 1]), "=f"(d[O + 2]), "=f"(d[O + 3]), "=f"(d[O + 4]), "=f"(d[O + 5]), "=f"(d[O + 6]), "=f"(d[O + 7]), "=f"(d[O + 8]), "=f"(d[O + 9]), "=f"(d[O + 10]), "=f"(d[O + 11]), "=f"(d[O + 12]), "=f"(d[O + 13]), "=f"(d[O + 14]), "=f"(d[O + 15]), "+l"(dd)
        : "r"(a0), "r"(a1), "r"(a2), "r"(a3), "n"(TB), "n"(INC));
}
template<int O, int TB, int SD, int INC, int SZ> __device__ __forceinline__ void wg_n32(float (&d)[SZ], uint32_t a0, uint32_t a1, uint32_t a2, uint32_t a3, uint64_t& dd) {
    if constexpr (SD == 1) wg_a32<O, TB, INC>(d, a0, a1, a2, a3, dd); else if constexpr (SD == 0) wg_z32<O, TB, INC>(d, a0, a1, a2, a3, dd);
}
template<int O, int TB, int INC, int SZ> __device__ __forceinline__ void wg_a64(float (&d)[SZ], uint32_t a0, uint32_t a1, uint32_t a2, uint32_t a3, uint64_t& dd) {
    asm volatile("{ .reg .pred p; setp.ne.b32 p, 1, 0;"
        "wgmma.mma_async.sync.aligned.m64n64k16.f32.bf16.bf16 {%0, %1, %2, %3, %4, %5, %6, %7, %8, %9, %10, %11, %12, %13, %14, %15, %16, %17, %18, %19, %20, %21, %22, %23, %24, %25, %26, %27, %28, %29, %30, %31}, "
        "{%33, %34, %35, %36}, %32, p, 1, 1, %37; add.s64 %32, %32, %38; }"
        : "+f"(d[O + 0]), "+f"(d[O + 1]), "+f"(d[O + 2]), "+f"(d[O + 3]), "+f"(d[O + 4]), "+f"(d[O + 5]), "+f"(d[O + 6]), "+f"(d[O + 7]), "+f"(d[O + 8]), "+f"(d[O + 9]), "+f"(d[O + 10]), "+f"(d[O + 11]), "+f"(d[O + 12]), "+f"(d[O + 13]), "+f"(d[O + 14]), "+f"(d[O + 15]), "+f"(d[O + 16]), "+f"(d[O + 17]), "+f"(d[O + 18]), "+f"(d[O + 19]), "+f"(d[O + 20]), "+f"(d[O + 21]), "+f"(d[O + 22]), "+f"(d[O + 23]), "+f"(d[O + 24]), "+f"(d[O + 25]), "+f"(d[O + 26]), "+f"(d[O + 27]), "+f"(d[O + 28]), "+f"(d[O + 29]), "+f"(d[O + 30]), "+f"(d[O + 31]), "+l"(dd)
        : "r"(a0), "r"(a1), "r"(a2), "r"(a3), "n"(TB), "n"(INC));
}
template<int O, int TB, int INC, int SZ> __device__ __forceinline__ void wg_z64(float (&d)[SZ], uint32_t a0, uint32_t a1, uint32_t a2, uint32_t a3, uint64_t& dd) {
    asm volatile("{ .reg .pred p; setp.ne.b32 p, 0, 0;"
        "wgmma.mma_async.sync.aligned.m64n64k16.f32.bf16.bf16 {%0, %1, %2, %3, %4, %5, %6, %7, %8, %9, %10, %11, %12, %13, %14, %15, %16, %17, %18, %19, %20, %21, %22, %23, %24, %25, %26, %27, %28, %29, %30, %31}, "
        "{%33, %34, %35, %36}, %32, p, 1, 1, %37; add.s64 %32, %32, %38; }"
        : "=f"(d[O + 0]), "=f"(d[O + 1]), "=f"(d[O + 2]), "=f"(d[O + 3]), "=f"(d[O + 4]), "=f"(d[O + 5]), "=f"(d[O + 6]), "=f"(d[O + 7]), "=f"(d[O + 8]), "=f"(d[O + 9]), "=f"(d[O + 10]), "=f"(d[O + 11]), "=f"(d[O + 12]), "=f"(d[O + 13]), "=f"(d[O + 14]), "=f"(d[O + 15]), "=f"(d[O + 16]), "=f"(d[O + 17]), "=f"(d[O + 18]), "=f"(d[O + 19]), "=f"(d[O + 20]), "=f"(d[O + 21]), "=f"(d[O + 22]), "=f"(d[O + 23]), "=f"(d[O + 24]), "=f"(d[O + 25]), "=f"(d[O + 26]), "=f"(d[O + 27]), "=f"(d[O + 28]), "=f"(d[O + 29]), "=f"(d[O + 30]), "=f"(d[O + 31]), "+l"(dd)
        : "r"(a0), "r"(a1), "r"(a2), "r"(a3), "n"(TB), "n"(INC));
}
template<int O, int TB, int INC, int SZ> __device__ __forceinline__ void wg_y64(float (&d)[SZ], uint32_t a0, uint32_t a1, uint32_t a2, uint32_t a3, uint64_t& dd) {
    asm volatile("{ .reg .pred p; setp.ne.b32 p, 0, 0;"
        "wgmma.mma_async.sync.aligned.m64n64k16.f32.bf16.bf16 {%0, %1, %2, %3, %4, %5, %6, %7, %8, %9, %10, %11, %12, %13, %14, %15, %16, %17, %18, %19, %20, %21, %22, %23, %24, %25, %26, %27, %28, %29, %30, %31}, "
        "{%33, %34, %35, %36}, %32, p, 1, 1, %37; add.s64 %32, %32, %38; }"
        : "+f"(d[O + 0]), "+f"(d[O + 1]), "+f"(d[O + 2]), "+f"(d[O + 3]), "+f"(d[O + 4]), "+f"(d[O + 5]), "+f"(d[O + 6]), "+f"(d[O + 7]), "+f"(d[O + 8]), "+f"(d[O + 9]), "+f"(d[O + 10]), "+f"(d[O + 11]), "+f"(d[O + 12]), "+f"(d[O + 13]), "+f"(d[O + 14]), "+f"(d[O + 15]), "+f"(d[O + 16]), "+f"(d[O + 17]), "+f"(d[O + 18]), "+f"(d[O + 19]), "+f"(d[O + 20]), "+f"(d[O + 21]), "+f"(d[O + 22]), "+f"(d[O + 23]), "+f"(d[O + 24]), "+f"(d[O + 25]), "+f"(d[O + 26]), "+f"(d[O + 27]), "+f"(d[O + 28]), "+f"(d[O + 29]), "+f"(d[O + 30]), "+f"(d[O + 31]), "+l"(dd)
        : "r"(a0), "r"(a1), "r"(a2), "r"(a3), "n"(TB), "n"(INC));
}
template<int O, int TB, int SD, int INC, int SZ> __device__ __forceinline__ void wg_n64(float (&d)[SZ], uint32_t a0, uint32_t a1, uint32_t a2, uint32_t a3, uint64_t& dd) {
    if constexpr (SD == 1) wg_a64<O, TB, INC>(d, a0, a1, a2, a3, dd); else if constexpr (SD == 0) wg_z64<O, TB, INC>(d, a0, a1, a2, a3, dd); else wg_y64<O, TB, INC>(d, a0, a1, a2, a3, dd);
}
__device__ __forceinline__ void wg_p64(float (&d)[32], uint32_t a0, uint32_t a1, uint32_t a2, uint32_t a3, uint64_t& dd, uint32_t sd) {
    asm volatile("{ .reg .pred p; setp.ne.b32 p, %37, 0;"
        "wgmma.mma_async.sync.aligned.m64n64k16.f32.bf16.bf16 {%0, %1, %2, %3, %4, %5, %6, %7, %8, %9, %10, %11, %12, %13, %14, %15, %16, %17, %18, %19, %20, %21, %22, %23, %24, %25, %26, %27, %28, %29, %30, %31}, "
        "{%33, %34, %35, %36}, %32, p, 1, 1, 1; add.s64 %32, %32, 128; }"
        : "+f"(d[0]), "+f"(d[1]), "+f"(d[2]), "+f"(d[3]), "+f"(d[4]), "+f"(d[5]), "+f"(d[6]), "+f"(d[7]), "+f"(d[8]), "+f"(d[9]), "+f"(d[10]), "+f"(d[11]), "+f"(d[12]), "+f"(d[13]), "+f"(d[14]), "+f"(d[15]), "+f"(d[16]), "+f"(d[17]), "+f"(d[18]), "+f"(d[19]), "+f"(d[20]), "+f"(d[21]), "+f"(d[22]), "+f"(d[23]), "+f"(d[24]), "+f"(d[25]), "+f"(d[26]), "+f"(d[27]), "+f"(d[28]), "+f"(d[29]), "+f"(d[30]), "+f"(d[31]), "+l"(dd)
        : "r"(a0), "r"(a1), "r"(a2), "r"(a3), "r"(sd));
}
template<int O, int TB, int INC, int SZ> __device__ __forceinline__ void wg_a128(float (&d)[SZ], uint32_t a0, uint32_t a1, uint32_t a2, uint32_t a3, uint64_t& dd) {
    asm volatile("{ .reg .pred p; setp.ne.b32 p, 1, 0;"
        "wgmma.mma_async.sync.aligned.m64n128k16.f32.bf16.bf16 {%0, %1, %2, %3, %4, %5, %6, %7, %8, %9, %10, %11, %12, %13, %14, %15, %16, %17, %18, %19, %20, %21, %22, %23, %24, %25, %26, %27, %28, %29, %30, %31, %32, %33, %34, %35, %36, %37, %38, %39, %40, %41, %42, %43, %44, %45, %46, %47, %48, %49, %50, %51, %52, %53, %54, %55, %56, %57, %58, %59, %60, %61, %62, %63}, "
        "{%65, %66, %67, %68}, %64, p, 1, 1, %69; add.s64 %64, %64, %70; }"
        : "+f"(d[O + 0]), "+f"(d[O + 1]), "+f"(d[O + 2]), "+f"(d[O + 3]), "+f"(d[O + 4]), "+f"(d[O + 5]), "+f"(d[O + 6]), "+f"(d[O + 7]), "+f"(d[O + 8]), "+f"(d[O + 9]), "+f"(d[O + 10]), "+f"(d[O + 11]), "+f"(d[O + 12]), "+f"(d[O + 13]), "+f"(d[O + 14]), "+f"(d[O + 15]), "+f"(d[O + 16]), "+f"(d[O + 17]), "+f"(d[O + 18]), "+f"(d[O + 19]), "+f"(d[O + 20]), "+f"(d[O + 21]), "+f"(d[O + 22]), "+f"(d[O + 23]), "+f"(d[O + 24]), "+f"(d[O + 25]), "+f"(d[O + 26]), "+f"(d[O + 27]), "+f"(d[O + 28]), "+f"(d[O + 29]), "+f"(d[O + 30]), "+f"(d[O + 31]), "+f"(d[O + 32]), "+f"(d[O + 33]), "+f"(d[O + 34]), "+f"(d[O + 35]), "+f"(d[O + 36]), "+f"(d[O + 37]), "+f"(d[O + 38]), "+f"(d[O + 39]), "+f"(d[O + 40]), "+f"(d[O + 41]), "+f"(d[O + 42]), "+f"(d[O + 43]), "+f"(d[O + 44]), "+f"(d[O + 45]), "+f"(d[O + 46]), "+f"(d[O + 47]), "+f"(d[O + 48]), "+f"(d[O + 49]), "+f"(d[O + 50]), "+f"(d[O + 51]), "+f"(d[O + 52]), "+f"(d[O + 53]), "+f"(d[O + 54]), "+f"(d[O + 55]), "+f"(d[O + 56]), "+f"(d[O + 57]), "+f"(d[O + 58]), "+f"(d[O + 59]), "+f"(d[O + 60]), "+f"(d[O + 61]), "+f"(d[O + 62]), "+f"(d[O + 63]), "+l"(dd)
        : "r"(a0), "r"(a1), "r"(a2), "r"(a3), "n"(TB), "n"(INC));
}
template<int O, int TB, int INC, int SZ> __device__ __forceinline__ void wg_z128(float (&d)[SZ], uint32_t a0, uint32_t a1, uint32_t a2, uint32_t a3, uint64_t& dd) {
    asm volatile("{ .reg .pred p; setp.ne.b32 p, 0, 0;"
        "wgmma.mma_async.sync.aligned.m64n128k16.f32.bf16.bf16 {%0, %1, %2, %3, %4, %5, %6, %7, %8, %9, %10, %11, %12, %13, %14, %15, %16, %17, %18, %19, %20, %21, %22, %23, %24, %25, %26, %27, %28, %29, %30, %31, %32, %33, %34, %35, %36, %37, %38, %39, %40, %41, %42, %43, %44, %45, %46, %47, %48, %49, %50, %51, %52, %53, %54, %55, %56, %57, %58, %59, %60, %61, %62, %63}, "
        "{%65, %66, %67, %68}, %64, p, 1, 1, %69; add.s64 %64, %64, %70; }"
        : "=f"(d[O + 0]), "=f"(d[O + 1]), "=f"(d[O + 2]), "=f"(d[O + 3]), "=f"(d[O + 4]), "=f"(d[O + 5]), "=f"(d[O + 6]), "=f"(d[O + 7]), "=f"(d[O + 8]), "=f"(d[O + 9]), "=f"(d[O + 10]), "=f"(d[O + 11]), "=f"(d[O + 12]), "=f"(d[O + 13]), "=f"(d[O + 14]), "=f"(d[O + 15]), "=f"(d[O + 16]), "=f"(d[O + 17]), "=f"(d[O + 18]), "=f"(d[O + 19]), "=f"(d[O + 20]), "=f"(d[O + 21]), "=f"(d[O + 22]), "=f"(d[O + 23]), "=f"(d[O + 24]), "=f"(d[O + 25]), "=f"(d[O + 26]), "=f"(d[O + 27]), "=f"(d[O + 28]), "=f"(d[O + 29]), "=f"(d[O + 30]), "=f"(d[O + 31]), "=f"(d[O + 32]), "=f"(d[O + 33]), "=f"(d[O + 34]), "=f"(d[O + 35]), "=f"(d[O + 36]), "=f"(d[O + 37]), "=f"(d[O + 38]), "=f"(d[O + 39]), "=f"(d[O + 40]), "=f"(d[O + 41]), "=f"(d[O + 42]), "=f"(d[O + 43]), "=f"(d[O + 44]), "=f"(d[O + 45]), "=f"(d[O + 46]), "=f"(d[O + 47]), "=f"(d[O + 48]), "=f"(d[O + 49]), "=f"(d[O + 50]), "=f"(d[O + 51]), "=f"(d[O + 52]), "=f"(d[O + 53]), "=f"(d[O + 54]), "=f"(d[O + 55]), "=f"(d[O + 56]), "=f"(d[O + 57]), "=f"(d[O + 58]), "=f"(d[O + 59]), "=f"(d[O + 60]), "=f"(d[O + 61]), "=f"(d[O + 62]), "=f"(d[O + 63]), "+l"(dd)
        : "r"(a0), "r"(a1), "r"(a2), "r"(a3), "n"(TB), "n"(INC));
}
template<int O, int TB, int SD, int INC, int SZ> __device__ __forceinline__ void wg_n128(float (&d)[SZ], uint32_t a0, uint32_t a1, uint32_t a2, uint32_t a3, uint64_t& dd) {
    if constexpr (SD == 1) wg_a128<O, TB, INC>(d, a0, a1, a2, a3, dd); else if constexpr (SD == 0) wg_z128<O, TB, INC>(d, a0, a1, a2, a3, dd);
}
__device__ __forceinline__ void wg_sa128(float (&d)[64], uint64_t& da, uint64_t& db) {
    asm volatile("{ .reg .pred p; setp.ne.b32 p, 1, 0;"
        "wgmma.mma_async.sync.aligned.m64n128k16.f32.bf16.bf16 {%0, %1, %2, %3, %4, %5, %6, %7, %8, %9, %10, %11, %12, %13, %14, %15, %16, %17, %18, %19, %20, %21, %22, %23, %24, %25, %26, %27, %28, %29, %30, %31, %32, %33, %34, %35, %36, %37, %38, %39, %40, %41, %42, %43, %44, %45, %46, %47, %48, %49, %50, %51, %52, %53, %54, %55, %56, %57, %58, %59, %60, %61, %62, %63}, "
        "%64, %65, p, 1, 1, 0, 1; add.s64 %64, %64, 128; add.s64 %65, %65, 128; }"
        : "+f"(d[0]), "+f"(d[1]), "+f"(d[2]), "+f"(d[3]), "+f"(d[4]), "+f"(d[5]), "+f"(d[6]), "+f"(d[7]), "+f"(d[8]), "+f"(d[9]), "+f"(d[10]), "+f"(d[11]), "+f"(d[12]), "+f"(d[13]), "+f"(d[14]), "+f"(d[15]), "+f"(d[16]), "+f"(d[17]), "+f"(d[18]), "+f"(d[19]), "+f"(d[20]), "+f"(d[21]), "+f"(d[22]), "+f"(d[23]), "+f"(d[24]), "+f"(d[25]), "+f"(d[26]), "+f"(d[27]), "+f"(d[28]), "+f"(d[29]), "+f"(d[30]), "+f"(d[31]), "+f"(d[32]), "+f"(d[33]), "+f"(d[34]), "+f"(d[35]), "+f"(d[36]), "+f"(d[37]), "+f"(d[38]), "+f"(d[39]), "+f"(d[40]), "+f"(d[41]), "+f"(d[42]), "+f"(d[43]), "+f"(d[44]), "+f"(d[45]), "+f"(d[46]), "+f"(d[47]), "+f"(d[48]), "+f"(d[49]), "+f"(d[50]), "+f"(d[51]), "+f"(d[52]), "+f"(d[53]), "+f"(d[54]), "+f"(d[55]), "+f"(d[56]), "+f"(d[57]), "+f"(d[58]), "+f"(d[59]), "+f"(d[60]), "+f"(d[61]), "+f"(d[62]), "+f"(d[63]), "+l"(da), "+l"(db));
}
__device__ __forceinline__ void wg_sz128(float (&d)[64], uint64_t& da, uint64_t& db) {
    asm volatile("{ .reg .pred p; setp.ne.b32 p, 0, 0;"
        "wgmma.mma_async.sync.aligned.m64n128k16.f32.bf16.bf16 {%0, %1, %2, %3, %4, %5, %6, %7, %8, %9, %10, %11, %12, %13, %14, %15, %16, %17, %18, %19, %20, %21, %22, %23, %24, %25, %26, %27, %28, %29, %30, %31, %32, %33, %34, %35, %36, %37, %38, %39, %40, %41, %42, %43, %44, %45, %46, %47, %48, %49, %50, %51, %52, %53, %54, %55, %56, %57, %58, %59, %60, %61, %62, %63}, "
        "%64, %65, p, 1, 1, 0, 1; add.s64 %64, %64, 128; add.s64 %65, %65, 128; }"
        : "=f"(d[0]), "=f"(d[1]), "=f"(d[2]), "=f"(d[3]), "=f"(d[4]), "=f"(d[5]), "=f"(d[6]), "=f"(d[7]), "=f"(d[8]), "=f"(d[9]), "=f"(d[10]), "=f"(d[11]), "=f"(d[12]), "=f"(d[13]), "=f"(d[14]), "=f"(d[15]), "=f"(d[16]), "=f"(d[17]), "=f"(d[18]), "=f"(d[19]), "=f"(d[20]), "=f"(d[21]), "=f"(d[22]), "=f"(d[23]), "=f"(d[24]), "=f"(d[25]), "=f"(d[26]), "=f"(d[27]), "=f"(d[28]), "=f"(d[29]), "=f"(d[30]), "=f"(d[31]), "=f"(d[32]), "=f"(d[33]), "=f"(d[34]), "=f"(d[35]), "=f"(d[36]), "=f"(d[37]), "=f"(d[38]), "=f"(d[39]), "=f"(d[40]), "=f"(d[41]), "=f"(d[42]), "=f"(d[43]), "=f"(d[44]), "=f"(d[45]), "=f"(d[46]), "=f"(d[47]), "=f"(d[48]), "=f"(d[49]), "=f"(d[50]), "=f"(d[51]), "=f"(d[52]), "=f"(d[53]), "=f"(d[54]), "=f"(d[55]), "=f"(d[56]), "=f"(d[57]), "=f"(d[58]), "=f"(d[59]), "=f"(d[60]), "=f"(d[61]), "=f"(d[62]), "=f"(d[63]), "+l"(da), "+l"(db));
}

constexpr uint32_t DH_W = 0x40000040u;
constexpr uint32_t DH_S = 8u;
constexpr uint32_t DH_V = 64u;

__device__ __forceinline__ uint64_t mkdesc(uint32_t lo, uint32_t hi) { uint64_t d; asm volatile("mov.b64 %0, {%1, %2};" : "=l"(d) : "r"(lo), "r"(hi)); return d; }
template<int N, int O, int NK, int A0, int Z, int LAST = 128, int K = 0, int SZ, int NA>
__device__ __forceinline__ void mma_w(float (&acc)[SZ], const uint32_t (&a)[NA], uint64_t& dd) {
    if constexpr (K < NK) {
        constexpr int i = (A0 + K) * 4, SD = (K == 0 && Z) ? 2 * (Z - 1) : 1, INC = K == NK - 1 ? LAST : 128;
        if constexpr (N == 32) wg_n32<O, 1, SD, INC>(acc, a[i], a[i + 1], a[i + 2], a[i + 3], dd);
        if constexpr (N == 64) wg_n64<O, 1, SD, INC>(acc, a[i], a[i + 1], a[i + 2], a[i + 3], dd);
        if constexpr (N == 128) wg_n128<O, 1, SD, INC>(acc, a[i], a[i + 1], a[i + 2], a[i + 3], dd);
        mma_w<N, O, NK, A0, Z, LAST, K + 1>(acc, a, dd);
    }
}
constexpr uint32_t SL16 = SLOT / 16;

struct Ctx {
    uint32_t smb;
    uint32_t warp, wg;
    const Maps* maps;
};

__device__ __forceinline__ void turn_wait(const Ctx& c) { asm volatile("bar.sync %0, 256;" :: "r"(1 + c.wg) : "memory"); }
__device__ __forceinline__ void turn_pass(const Ctx& c) { asm volatile("bar.arrive %0, 256;" :: "r"(2 - c.wg) : "memory"); }

__device__ __forceinline__ void issue_item(const Ctx& c, uint32_t item) {
    uint32_t e0, e1, e2, e3;
    lds128(e0, e1, e2, e3, c.smb + O_TAB + item * 16);
    tma3d(e0, (const char*)c.maps + e1, e2, e3, c.smb + O_FULL + item * 8);
}
__device__ __forceinline__ void tma3d_if(uint32_t dst, const void* m, int blk, int row, uint32_t bar, uint32_t a, uint32_t b) {
    asm volatile("{ .reg .pred p, q; elect.sync _|q, 0xffffffff; setp.eq.and.u32 p, %6, %7, q;\n"
        "@p cp.async.bulk.tensor.3d.shared::cluster.global.mbarrier::complete_tx::bytes [%0], [%1, {%5, %4, %3}], [%2]; }"
        :: "r"(dst), "l"(m), "r"(bar), "r"(blk), "r"(row), "r"(0), "r"(a), "r"(b) : "memory");
}
__device__ __forceinline__ void part_if(uint32_t dst, const void* m, int arr, int row, int col, uint32_t bar, uint32_t bytes, uint32_t u) {
    asm volatile("{ .reg .pred p, q; elect.sync _|q, 0xffffffff; setp.eq.and.u32 p, %7, 0, q;\n"
        "@p mbarrier.arrive.expect_tx.shared::cta.b64 _, [%2], %6;\n"
        "@p cp.async.bulk.tensor.3d.shared::cluster.global.mbarrier::complete_tx::bytes [%0], [%1, {%5, %4, %3}], [%2]; }"
        :: "r"(dst), "l"(m), "r"(bar), "r"(arr), "r"(row), "r"(col), "r"(bytes), "r"(u) : "memory");
}
__device__ __forceinline__ void part1_if(uint32_t dst, const void* m, int arr, int row, uint32_t bar, uint32_t u) {
    asm volatile("{ .reg .pred p, q; elect.sync _|q, 0xffffffff; setp.eq.and.u32 p, %6, 0, q;\n"
        "@p cp.async.bulk.tensor.3d.shared::cluster.global.mbarrier::complete_tx::bytes [%0], [%1, {%5, %4, %3}], [%2]; }"
        :: "r"(dst), "l"(m), "r"(bar), "r"(arr), "r"(row), "r"(64), "r"(u) : "memory");
}
template<int K>
__device__ __forceinline__ void release(const Ctx& c, uint32_t item) {
    if (c.warp == 4 + K) { if (elect_one()) issue_item(c, item + 4); }
}
__device__ __forceinline__ void wait_item(const Ctx& c, uint32_t item) { mbar_wait(c.smb + O_FULL + item * 8, 0); }

template<int N, int SZ>
__device__ __forceinline__ void block448_tail(const Ctx& c, float (&acc)[SZ], const uint32_t (&xa)[112], uint32_t it, uint32_t dlo) {
    uint64_t dd = mkdesc(dlo, DH_W);
    mma_w<N, 0, 14, 0, 1>(acc, xa, dd);
    wg_commit();
    wait_item(c, it + 1);
    mma_w<N, 0, 14, 14, 0>(acc, xa, dd);
    wg_commit();
    turn_pass(c);
}

template<int O, bool TAG, int SZ>
__device__ __forceinline__ void stage_rows(uint32_t addr, uint32_t off, const float (&a)[SZ], uint32_t par = 0) {
    #pragma unroll
    for (int t = 0; t < 4; t++) {
        const int o = O + t * 8;
        uint32_t v0 = pack2(a[o], a[o + 1]), v1 = pack2(a[o + 2], a[o + 3]);
        if (TAG && t == 0) { v0 = (v0 & ~1u) | par; v1 = (v1 & ~1u) | par; }
        stsm4((addr ^ (t * 32)) + off, v0, v1, pack2(a[o + 4], a[o + 5]), pack2(a[o + 6], a[o + 7]));
    }
}

struct AttC { float rk[4]; float rq[2]; uint32_t mcur; bool c0, c1; uint32_t w; };

template<int W> __device__ __forceinline__ void pick(const float (&s)[32], float (&v)[4], const AttC& a) {
    v[0] = (W == 0 || a.c0) ? s[8 * W] : s[(8 * W - 4) & 31]; v[1] = (W == 0 || a.c1) ? s[8 * W + 1] : s[(8 * W - 3) & 31];
    v[2] = a.c0 ? s[8 * W + 6] : s[8 * W + 2]; v[3] = a.c1 ? s[8 * W + 7] : s[8 * W + 3];
}
template<int W> __device__ __forceinline__ void place(uint32_t (&pa)[16], const uint32_t (&x)[4]) {
    pa[4 * W] = x[0]; pa[4 * W + 1] = x[1]; pa[4 * W + 3] = x[3];
    if (W > 0) pa[(4 * W - 2) & 15] = x[2];
}
template<int H> __device__ __forceinline__ void soft1(float (&v)[H][4], const AttC& a) {
    float m[H][2];
    #pragma unroll
    for (int h = 0; h < H; h++) {
        #pragma unroll
        for (int i = 0; i < 4; i++) v[h][i] = fmaf(v[h][i], a.rk[i], fminf(a.rk[i], 0.f));
        m[h][0] = fmaxf(v[h][0], v[h][1]); m[h][1] = fmaxf(v[h][2], v[h][3]);
    }
    #pragma unroll
    for (int d = 1; d < 3; d++) {
        #pragma unroll
        for (int i = 0; i < 2 * H; i++) m[i >> 1][i & 1] = fmaxf(m[i >> 1][i & 1], __shfl_xor_sync(0xffffffffu, m[i >> 1][i & 1], d));
    }
    #pragma unroll
    for (int i = 0; i < 4 * H; i++) v[i >> 2][i & 3] = ex2(v[i >> 2][i & 3] - m[i >> 2][(i >> 1) & 1]);
}
template<int H> __device__ __forceinline__ void soft2(const float (&v)[H][4], float (&s)[H][2]) {
    #pragma unroll
    for (int i = 0; i < 2 * H; i++) s[i >> 1][i & 1] = v[i >> 1][2 * (i & 1)] + v[i >> 1][2 * (i & 1) + 1];
    #pragma unroll
    for (int d = 1; d < 3; d++) {
        #pragma unroll
        for (int i = 0; i < 2 * H; i++) s[i >> 1][i & 1] += __shfl_xor_sync(0xffffffffu, s[i >> 1][i & 1], d);
    }
}
__device__ __forceinline__ void soft3(const float (&v)[4], const float (&s)[2], uint32_t (&x)[4], const AttC& a) {
    const float s0 = rcp(s[0] * a.rq[0]), s1 = rcp(s[1] * a.rq[1]);
    const uint32_t plo = pack2(v[0] * a.rk[0] * s0, v[1] * a.rk[1] * s0), phi = pack2(v[2] * a.rk[2] * s1, v[3] * a.rk[3] * s1);
    x[0] = plo & a.mcur; x[2] = plo & ~a.mcur; x[3] = phi & a.mcur; x[1] = phi & ~a.mcur;
}
__device__ __forceinline__ void pick_w(const float (&s)[32], float (&v)[4], const AttC& a) {
    if (a.w == 0) pick<0>(s, v, a); else if (a.w == 1) pick<1>(s, v, a); else if (a.w == 2) pick<2>(s, v, a); else pick<3>(s, v, a);
}
__device__ __forceinline__ void softmax_head(const float (&s)[32], uint32_t (&pa)[16], const AttC& a) {
    float v[1][4], t[1][2]; uint32_t x[1][4];
    pick_w(s, v[0], a);
    soft1<1>(v, a); soft2<1>(v, t); soft3(v[0], t[0], x[0], a);
    if (a.w == 0) place<0>(pa, x[0]); else if (a.w == 1) place<1>(pa, x[0]); else if (a.w == 2) place<2>(pa, x[0]); else place<3>(pa, x[0]);
}
__device__ __forceinline__ void place2(uint32_t (&pa)[16], uint32_t (&pb)[16], const uint32_t (&x)[4], const uint32_t (&y)[4], const AttC& a) {
    if (a.w == 0) { place<0>(pa, x); place<0>(pb, y); } else if (a.w == 1) { place<1>(pa, x); place<1>(pb, y); }
    else if (a.w == 2) { place<2>(pa, x); place<2>(pb, y); } else { place<3>(pa, x); place<3>(pb, y); }
}
__device__ __forceinline__ void mma_s(float (&s)[32], const uint32_t (&q)[8], uint32_t dlo) {
    uint64_t dd = mkdesc(dlo, DH_S);
    wg_n64<0, 0, 2, 128>(s, q[0], q[1], q[2], q[3], dd);
    wg_n64<0, 0, 1, 0>(s, q[4], q[5], q[6], q[7], dd);
}
__device__ __forceinline__ void mma_pv(float (&o)[16], const uint32_t (&p)[16], uint32_t dlo) {
    uint64_t dd = mkdesc(dlo, DH_V);
    wg_n32<0, 1, 0, 16>(o, p[0], p[1], p[2], p[3], dd);
    wg_n32<0, 1, 1, 16>(o, p[4], p[5], p[6], p[7], dd);
    wg_n32<0, 1, 1, 16>(o, p[8], p[9], p[10], p[11], dd);
    wg_n32<0, 1, 1, 0>(o, p[12], p[13], p[14], p[15], dd);
}
__device__ __forceinline__ uint32_t wrap14(uint32_t b) { return b >= 14 ? b - 14 : b; }
__device__ __forceinline__ void stage(const float (&m)[32], uint32_t base, uint32_t p0) {
    #pragma unroll
    for (int i = 0; i < 8; i += 2)
        stsm4(base + wrap14(p0 + i) * 1024, pack2(m[4 * i], m[4 * i + 1]), pack2(m[4 * i + 2], m[4 * i + 3]),
              pack2(m[4 * i + 4], m[4 * i + 5]), pack2(m[4 * i + 6], m[4 * i + 7]));
}
__device__ __forceinline__ void load_qa(uint32_t (&q)[8], uint32_t addr, bool qlow) {
    ldsm4(q[0], q[1], q[2], q[3], addr); ldsm4(q[4], q[5], q[6], q[7], addr + 2048);
    q[6] = qlow ? q[6] : 0u; q[7] = qlow ? q[7] : 0u;
}
__device__ __forceinline__ void load_qb(uint32_t (&q)[8], uint32_t addr, bool qlow) {
    ldsm4(q[0], q[1], q[2], q[3], addr + 3072); ldsm4(q[4], q[5], q[6], q[7], addr + 5120);
    q[0] = qlow ? 0u : q[0]; q[1] = qlow ? 0u : q[1];
}
__device__ __forceinline__ void store_oa(const float (&o)[16], uint32_t addr, uint32_t (&h3)[2]) {
    stsm4(addr, pack2(o[0], o[1]), pack2(o[2], o[3]), pack2(o[4], o[5]), pack2(o[6], o[7]));
    stsm2(addr + 2048, pack2(o[8], o[9]), pack2(o[10], o[11]));
    h3[0] = pack2(o[12], o[13]); h3[1] = pack2(o[14], o[15]);
}
__device__ __forceinline__ void store_ob(const float (&o)[16], uint32_t addr, const uint32_t (&h3)[2], bool qlow) {
    uint32_t b0 = pack2(o[0], o[1]), b1 = pack2(o[2], o[3]);
    stsm4(addr + 3072, qlow ? h3[0] : b0, qlow ? h3[1] : b1, pack2(o[4], o[5]), pack2(o[6], o[7]));
    stsm4(addr + 5120, pack2(o[8], o[9]), pack2(o[10], o[11]), pack2(o[12], o[13]), pack2(o[14], o[15]));
}
__device__ __forceinline__ void pack_o(uint32_t (&k)[14], const float (&o)[16], const float (&u)[16], bool qlow) {
    #pragma unroll
    for (int i = 0; i < 6; i++) { k[i] = pack2(o[2 * i], o[2 * i + 1]); k[8 + i] = pack2(u[4 + 2 * i], u[5 + 2 * i]); }
    k[6] = pack2(qlow ? o[12] : u[0], qlow ? o[13] : u[1]); k[7] = pack2(qlow ? o[14] : u[2], qlow ? o[15] : u[3]);
    #pragma unroll
    for (int i = 0; i < 14; i++) asm volatile("" : "+r"(k[i]) :: "memory");
}
__device__ __forceinline__ void store_o(const uint32_t (&k)[14], uint32_t addr) {
    stsm4(addr, k[0], k[1], k[2], k[3]); stsm4(addr + 2048, k[4], k[5], k[6], k[7]);
    stsm4(addr + 4096, k[8], k[9], k[10], k[11]); stsm2(addr + 6144, k[12], k[13]);
}
__device__ __forceinline__ void mma_early(float (&acc)[64], uint32_t alo, uint32_t blo) {
    uint64_t da = mkdesc(alo, DH_S), db = mkdesc(blo, DH_W);
    wg_sz128(acc, da, db);
    #pragma unroll
    for (int k = 1; k < 7; k++) wg_sa128(acc, da, db);
}
__device__ __forceinline__ void load_x_tile(uint32_t (&xa)[112], float& rs_lo, float& rs_hi, const Ctx& c, uint32_t lane, uint32_t pf0, uint32_t pf1) {
    const uint32_t smb = c.smb, warp = c.warp;
    float sm[4][4];
    #pragma unroll
    for (int i = 0; i < 16; i++) sm[i >> 2][i & 3] = 0.f;
    const uint32_t la = smb + XR + warp * 14336 + (lane & 15) * 128;
    const uint32_t lx = ((lane >> 4) ^ (lane & 7)) * 16;
    mbar_wait(smb + O_XFULL + warp * 8, 0);
    PT(23);
    #pragma unroll
    for (int k = 0; k < 28; k++) ldsm4(xa[4 * k], xa[4 * k + 1], xa[4 * k + 2], xa[4 * k + 3], la + (k >> 2) * 2048 + (lx ^ ((k & 3) * 32)));
    #pragma unroll
    for (int k = 0; k < 28; k++) hmma(sm[k & 3], xa[4 * k], xa[4 * k + 1], xa[4 * k + 2], xa[4 * k + 3], 0x3f803f80u, 0x3f803f80u);
    if (c.wg == 1) asm volatile("bar.arrive 1, 256;" ::: "memory");
    mbar_wait(smb + O_XFULL + warp * 8, 0);
    const float mlo = ((sm[0][0] + sm[1][0]) + (sm[2][0] + sm[3][0])) * (1.f / 448.f), mhi = ((sm[0][2] + sm[1][2]) + (sm[2][2] + sm[3][2])) * (1.f / 448.f);
    const uint32_t mbl = pack2(mlo, mlo), mbh = pack2(mhi, mhi);
    uint32_t sq[16];
    #pragma unroll
    for (int i = 0; i < 112; i++) {
        xa[i] = hsub2(xa[i], (i & 1) ? mbh : mbl);
        sq[i & 15] = i < 16 ? hmul2(xa[i], xa[i]) : hfma2(xa[i], xa[i], sq[i & 15]);
    }
    float ql[2] = {0.f, 0.f}, qh[2] = {0.f, 0.f};
    #pragma unroll
    for (int i = 0; i < 16; i++) { ql[i & 1] += bf_lo(sq[i]); qh[i & 1] += bf_hi(sq[i]); }
    float vl = ql[0] + qh[0], vh = ql[1] + qh[1];
    vl += __shfl_xor_sync(0xffffffffu, vl, 1); vh += __shfl_xor_sync(0xffffffffu, vh, 1);
    vl += __shfl_xor_sync(0xffffffffu, vl, 2); vh += __shfl_xor_sync(0xffffffffu, vh, 2);
    const float dl = mlo - bf_lo(mbl), dh = mhi - bf_lo(mbh);
    vl = fmaxf(vl * (1.f / 448.f) - dl * dl, 0.f); vh = fmaxf(vh * (1.f / 448.f) - dh * dh, 0.f);
    rs_lo = rcp(bf_round(sqrt_fast(bf_round(bf_round(vl) + 1e-5f))));
    rs_hi = rcp(bf_round(sqrt_fast(bf_round(bf_round(vh) + 1e-5f))));
    if (warp == 5) {
        if (elect_one()) {
            uint32_t e0, e1, e2, e3;
            lds128(e0, e1, e2, e3, smb + O_TAB + pf0 * 16);
            tma3d_pf((const char*)c.maps + e1, e2, e3);
            lds128(e0, e1, e2, e3, smb + O_TAB + pf1 * 16);
            tma3d_pf((const char*)c.maps + e1, e2, e3);
        }
        __syncwarp();
    }
}

__global__ void __cluster_dims__(2, 1, 1) __launch_bounds__(256, 1)
fused_kernel(const __grid_constant__ Maps maps, const char* __restrict__ xg, uint4* __restrict__ out128, uint4* __restrict__ part) {
    PT0A();
    extern __shared__ __align__(1024) uint8_t smraw[];
    const uint32_t smb = (uint32_t)__cvta_generic_to_shared(smraw);
    const uint32_t tid = threadIdx.x, lane = tid & 31;
    const uint32_t warp = __shfl_sync(0xffffffffu, tid >> 5, 0);
    const uint32_t wg = warp >> 2, w = warp & 3;
    const uint32_t r = blockIdx.x & 1, pair = blockIdx.x >> 1;
    const bool is_ffn = pair < 48;
    const uint32_t p = pair >> 4;
    const int T0 = is_ffn ? (int)(pair & 15) * 128 : (int)(pair - 48) * 114 - 14;
    Ctx c{smb, warp, wg, &maps};
    PT0B(); GT(46);

    const uint32_t fb = p < 2 ? (2 * p + r) * 5 : 20 + 4 * r;
    if (warp == ISS) {
        const bool e = elect_one();
        if (e) {
            #pragma unroll
            for (int i = 0; i < 12; i++) mbar_init(smb + O_XFULL + i * 8, 1);
            asm volatile("fence.mbarrier_init.release.cluster;" ::: "memory");
            #pragma unroll
            for (int i = 0; i < 12; i++) mbar_expect_tx(smb + O_XFULL + i * 8, i < 8 ? 14336 : SLOT);
        }
        __syncwarp();
        asm volatile("bar.arrive 3, 256;" ::: "memory");
        if (e) {
            const int xr = T0 >> 1;
            #pragma unroll
            for (int i = 0; i < 8; i++) tma4d(smb + XR + i * 14336, &maps.m[0], xr + (i & 3) * 16, 0, i >> 2, smb + O_XFULL + i * 8);
            const char* const ma = (const char*)&maps + (p < 2 ? 384 : 128);
            const char* const mb = (const char*)&maps + (p < 2 ? 512 : 128);
            const uint32_t ba = p < 2 ? fb + 1 : is_ffn ? 3 + 14 * r : 6 * r, bb = p < 2 ? fb + 1 : is_ffn ? 10 + 7 * r : 6 * r + 7;
            tma3d(smb, ma, ba, 0, smb + O_FULL);
            tma3d(smb + SLOT, ma, ba, 224, smb + O_FULL + 8);
            tma3d(smb + 2 * SLOT, mb, bb, 0, smb + O_FULL + 16);
            tma3d(smb + 3 * SLOT, mb, bb, 224, smb + O_FULL + 24);
        }
        __syncwarp();
    } else {
        const uint32_t i = tid - 32;
        if (i < 64 && (i & 7) < 7 && blockIdx.x < 128) asm volatile("prefetch.global.L2 [%0];" :: "l"(xg + (blockIdx.x * 8 + (i >> 3)) * 1792 + (i & 7) * 128) : "memory");
        if (warp == 3) {
            if (elect_one()) {
                #pragma unroll
                for (int i = 4; i < 42; i++) mbar_init(smb + O_FULL + i * 8, 1);
                asm volatile("fence.mbarrier_init.release.cluster;" ::: "memory");
            }
            __syncwarp();
            if (lane < 8) mbar_expect_tx(smb + O_RECV + lane * 8, is_ffn ? 8192 : 12288);
        }
    }
    uint32_t* const flags = (uint32_t*)part;
    uint32_t* const fl = flags + blockIdx.x * FST + warp;
    const uint32_t seq = p == 0 ? (r ? 0x1062354u : 0x0162354u) : p == 1 ? (r ? 0x5462310u : 0x4562310u) : (r ? 0x2365410u : 0x3265410u);
    PT(21);
    if (warp != ISS) asm volatile("bar.sync 3, 256;" ::: "memory");
    if (warp == 5) {
        const uint32_t i = lane + 4;
        if (i < 34) {
            uint32_t e0 = (i & 3) * SLOT, e1, e2, e3 = (i & 1) * 224, by = SLOT;
            if (is_ffn) {
                const bool p1 = i < 20, sm = p == 2 && !(i & 1);
                by = p1 ? SLOT : sm ? 12288 : SLOT2;
                e0 = p1 ? e0 : (i % 5) * SLOT2;
                e1 = p1 ? ((i & 2) ? 512 : 384) : sm ? 768 : 640;
                e2 = p1 ? fb + (i >= 16 ? 0 : (i >> 2) + (p < 2)) : (seq >> (2 * ((i - 20) & 14))) & 15;
                e3 = p1 ? e3 : fb * 64 + (~i & 1) * 160;
            } else {
                const uint32_t j = i / 6, sub = i - 6 * j;
                e1 = i < 18 ? 128 : i < 24 ? 896 : 256;
                e2 = i < 18 ? 7 * (sub >> 1) + (r ? 6 - j : j) : i < 24 ? (0x224040u >> (4 * sub)) & 15 : 6;
                e3 = i < 18 ? e3 : r * 224 + (i < 24 && ((0x13u >> sub) & 1) == r ? 112 : 0);
            }
            sts128(smb + O_TAB + i * 16, smb + e0, e1, e2, e3);
            mbar_expect_tx(smb + O_FULL + i * 8, by);
        }
        __syncwarp();
    }
    if (tid == 255) asm volatile("st.shared.u32 [%0], %1;" :: "r"(smb + O_EPOCH), "r"((ld_flag(fl) & ~7u) + 8) : "memory");
    PT(22);

    const uint32_t dring = (smb & 0x3FFFF) >> 4;
    const uint32_t wr = smb + XR + warp * 14336;

    float acc[32];
    uint32_t blk, grow, fpar, par, fv, need, xv[16], tq[4], pq, oq, xph = 1;
    uint4* op;
    uint32_t iss = 0;
    const uint32_t* fp;
    const uint32_t xbar = smb + O_XFULL + warp * 8, sbar = smb + O_FULL + 80 + warp * 8, lbar0 = smb + O_RECV + wg * 32;
    auto final_deps = [&](uint32_t lane, uint32_t rr, uint32_t na, uint32_t n01, uint32_t n2) {
        const uint32_t row = grow + min((lane & 6) * 4, 15u), t = (row * 1150) >> 16;
        const bool at = lane < 6;
        fp = flags + (at ? 96 + 2 * t + (lane & 1) : 32 * min(lane >> 1, 5u) - 96 + 2 * (grow >> 6) + rr) * FST + fpar * 4 + (at ? (row - 57 * t + 7) >> 4 : w);
        need = at ? na : lane < 10 ? n01 : n2;
        op = out128 + (fpar + 2 * (grow + (lane >> 3))) * 56 + blk * 8 + (lane & 7);
        pq = wr + lane * 16;
        asm volatile("" : "+r"(need), "+l"(fp), "+l"(op), "+r"(pq));
        fv = need - 1;
    };
    auto apoll = [&]() { asm volatile("{ .reg .pred p; setp.lt.s32 p, %2, 0; @p cp.async.cg.shared.global [%0 + 8192], [%1], 16; }" :: "r"(pq), "l"((size_t)fp & ~(size_t)15), "r"(fv - need) : "memory"); };
    auto ainit = [&]() { asm volatile("st.shared.u32 [%0 + 8192], %1;" :: "r"(pq + ((uint32_t)(size_t)fp & 12)), "r"(need - 1) : "memory"); };
    auto aread = [&]() { asm volatile("{ .reg .pred p; setp.lt.s32 p, %2, 0; @p ld.volatile.shared.u32 %0, [%1 + 8192]; }" : "+r"(fv) : "r"(pq + ((uint32_t)(size_t)fp & 12)), "r"(fv - need) : "memory"); };
    auto final_loads = [&](uint32_t blk, uint32_t m, uint32_t bytes) {
        const uint32_t up = (m | iss) & 0xfc0, us = (m | iss) & 0x3f;
        part_if(wr, &maps.m[9], ((blk & 6) + fpar) * 4, grow, (blk & 1) * 64, xbar, bytes, up);
        part_if(wr + 4096, &maps.m[9], ((blk & 6) + fpar) * 4 + 2, grow, (blk & 1) * 64, sbar, 4096, us);
        iss |= (up ? 0 : 0xfc0) | (us ? 0 : 0x3f);
    };
    auto final_x = [&](uint32_t lane, uint32_t off) {
        const uint32_t tf = wr + (lane & 15) * 128 + ((lane >> 4) ^ (lane & 7)) * 16;
        oq = pq ^ ((lane >> 3) * 16);
        asm volatile("" : "+r"(oq));
        #pragma unroll
        for (int t = 0; t < 4; t++) {
            tq[t] = tf ^ (t * 32);
            asm volatile("" : "+r"(tq[t]));
            lds128(xv[4 * t], xv[4 * t + 1], xv[4 * t + 2], xv[4 * t + 3], (oq ^ ((t & 1) * 64)) + off + t * 512);
        }
    };

    uint32_t xa[112];
    float rs_lo, rs_hi;
    load_x_tile(xa, rs_lo, rs_hi, c, lane, is_ffn ? 4 + (pair & 15) : pair - 44, is_ffn ? min(20 + (pair & 15), 33u) : min(pair - 26, 24u));
    PT(1);
    if (is_ffn) {
        const uint32_t tile = pair & 15;
        grow = tile * 64 + w * 16; fpar = wg;
        uint32_t sg[16];
        const float hl = 0.5f * rs_lo, hh = 0.5f * rs_hi;
        const uint32_t pw = wr + lane * 16;
        uint32_t it = 0, base = 0, sp = pw, lbar = smb + O_FULL + wg * 40, raddr, rbar, pc;
        uint4* po;
        blk = seq >> 24;
        #pragma unroll 1
        while (true) {
            const bool ex = p == 2 && it == 0;
            wait_item(c, it); turn_wait(c); wg_fence();
            block448_tail<64>(c, acc, xa, it, dring);
            wg_wait<1>(); release<0>(c, it);
            if (__builtin_expect(it >= 8, 0)) {
            if (it == 8) {
                asm volatile("ld.shared.u32 %0, [%1];" : "=r"(base) : "r"(smb + O_EPOCH) : "memory");
                if (lane == 0) asm volatile("st.relaxed.gpu.global.u32 [%0], %1;" :: "l"(fl), "r"(base + 1) : "memory");
                if (elect_one()) tma4d(wr + 4 * 2048, &maps.m[8], grow, blk, wg, lbar0 + 24);
                if (warp == 7 && elect_one()) {
                    #pragma unroll
                    for (int j = 0; j < 12; j++) if ((PH >> j) & 1) asm volatile("prefetch.tensormap [%0];" :: "l"(&maps.m[j]) : "memory");
                }
                if (tid >= 246) mbar_expect_tx(smb + O_FULL + (tid - 246) * 8, 4096);
                asm volatile("barrier.cluster.arrive.relaxed.aligned;" ::: "memory");
            } else if (it == 12) {
                asm volatile("barrier.cluster.wait.aligned;" ::: "memory");
                raddr = mapa(pw + 5 * 2048, r ^ 1); rbar = mapa(lbar, r ^ 1);
                const uint32_t ln = lane + (base & 7), pp = p + (base & 7), sz = seq + (base & 7);
                final_deps(ln, ln & 1, base + 1 + (p >> 1), base + 2 + r + (p & 2), base + 2 + r + (p ? 2 : 0));
                par = (base >> 3) & 1;
                asm volatile("" : "+r"(par));
                pc = 0;
                uint32_t e0 = 0;
                #pragma unroll
                for (int k = 0; k < 5; k++) {
                    const uint32_t b = k < 4 ? (sz >> (4 * k)) & 15 : pp == 2 ? 7 : FB, j = k < 4 ? (pp + (k >> 1)) >> 1 : pp & 1;
                    const uint32_t e = ((b & 6) * 4 + j) * 4 + (b & 1);
                    if (k) pc |= (e - e0 + 129) << (8 * k - 8);
                    else po = part + (G_S + (wg * 4 + (e >> 2)) * (SROWS * 16) + (grow + 8 * r + (ln >> 3)) * 16 + (ln & 7));
                    e0 = e;
                }
                asm volatile("" : "+l"(po), "+r"(pc));
            } else { mbar_wait(lbar0 + 24, 0); final_x(lane + (base & 7), 4 * 2048); }
            }
            wg_wait<0>(); release<1>(c, it + 1); pin<0, 32>(acc);
            if (!ex) {
                #pragma unroll
                for (int i = 0; i < 32; i++) {
                    const float a = acc[i] * ((i & 2) ? hh : hl);
                    acc[i] = fmaf(a, tanh_fast(a), a);
                }
            }
            #pragma unroll
            for (int i = 0; i < 16; i++) sg[i] = pack2(acc[2 * i], acc[2 * i + 1]);
            wait_item(c, it + 2); turn_wait(c); wg_fence();
            block448_tail<64>(c, acc, xa, it + 2, dring + 2 * SL16);
            wg_wait<1>(); release<2>(c, it + 2);
            it += 4;
            if (it == 20) break;
            wg_wait<0>(); release<3>(c, it - 1); pin<0, 32>(acc);
            if (ex) {
                uint32_t* const e = (uint32_t*)(part + G_E + (4 * r + wg) * 8 * SROWS + grow + 8) + lane;
                #pragma unroll
                for (int i = 0; i < 16; i++) {
                    e[(i >> 1) * SROWS * 4 + (i & 1) * 32] = sg[i];
                    if (!r) e[(16 + (i >> 1)) * SROWS * 4 + (i & 1) * 32] = pack2(acc[2 * i], acc[2 * i + 1]);
                }
            } else {
                #pragma unroll
                for (int i = 0; i < 16; i++) sg[i] = hmul2(sg[i], pack2(acc[2 * i] * ((i & 1) ? hh : hl), acc[2 * i + 1] * ((i & 1) ? hh : hl)));
                #pragma unroll
                for (int t = 0; t < 4; t++) sts128(sp + t * 512, sg[4 * t], sg[4 * t + 1], sg[4 * t + 2], sg[4 * t + 3]);
                sp += 2048;
            }
            PT(1 + (it >> 2));
        }
        PT2(13);
        tma3d_if(smb + 3 * SLOT2, &maps.m[5], (seq >> 4) & 15, fb * 64, smb + O_FULL + 23 * 8, warp, 5);
        uint32_t ha[80];
        #pragma unroll
        for (int t = 0; t < 16; t++) lds128(ha[16 + 4 * t], ha[17 + 4 * t], ha[18 + 4 * t], ha[19 + 4 * t], pw + t * 512);
        PT2(14);
        wait_item(c, it);
        PT2(45);
        wg_wait<0>(); pin<0, 32>(acc);
        #pragma unroll
        for (int i = 0; i < 16; i++) ha[i] = hmul2(sg[i], pack2(acc[2 * i] * ((i & 1) ? hh : hl), acc[2 * i + 1] * ((i & 1) ? hh : hl)));
        PT(6);
        uint32_t pk[16], sa = 0, sb = 4 * SLOT2 / 16, sq = seq >> 8;
        const CUtensorMap* const mw = &maps.m[p == 2 && !wg ? 6 : 5];
        uint32_t wv[8];
        auto get = [&](uint32_t n) {
            const uint32_t a = pw + 5 * 2048 + (~n & 1) * 1024;
            mbar_wait(lbar, 1);
            lds128(wv[0], wv[1], wv[2], wv[3], a); lds128(wv[4], wv[5], wv[6], wv[7], a + 512);
        };
        auto put = [&](uint32_t n) {
            #pragma unroll
            for (int i = 0; i < 8; i++) pk[i] = hadd2(wv[i], pk[i]);
            pk[0] = (pk[0] & ~1u) | par; pk[4] = (pk[4] & ~1u) | par;
            #pragma unroll
            for (int t = 0; t < 2; t++)
                asm volatile("st.relaxed.gpu.global.v4.u32 [%0], {%1,%2,%3,%4};" :: "l"(po + t * 64), "r"(pk[4 * t]), "r"(pk[4 * t + 1]), "r"(pk[4 * t + 2]), "r"(pk[4 * t + 3]) : "memory");
            if (lane == 0) asm volatile("st.relaxed.gpu.global.u32 [%0], %1;" :: "l"(fl), "r"(base + n + 1) : "memory");
        };
        #pragma unroll 1
        for (uint32_t n = 0; ; n++, it += 2, sq >>= 4) {
            uint64_t dd = mkdesc(dring + sa + 6 * 128, DH_W), de = mkdesc(dring + sa, DH_W);
            const uint32_t sf = wg ? sa : sb;
            sb = sa == 4 * SLOT2 / 16 ? 0 : sa + SLOT2 / 16;
            sa = sb == 4 * SLOT2 / 16 ? 0 : sb + SLOT2 / 16;
            turn_wait(c); wg_fence();
            if (n >= 5) fv = ld_flag(fp);
            if (p < 2) mma_w<64, 0, 4, 16, 2>(acc, ha, dd);
            wg_p64(acc, ha[40], ha[41], ha[42], ha[43], de, p < 2);
            mma_w<64, 0, 5, 11, 0>(acc, ha, de);
            wg_commit();
            de = mkdesc(dring + sb, DH_W);
            if (n * wg == 5) { get(5); put(5); }
            wait_item(c, it + 1); PT(38 + n);
            mma_w<64, 0, 10 - EP, 0, 0>(acc, ha, de);
            asm volatile("{ .reg .pred p; setp.lt.u32 p, %1, 7; @p bar.arrive %0, 256; }" :: "r"(2 - wg), "r"(n + wg) : "memory");
            mma_w<64, 0, EP, 10 - EP, 0>(acc, ha, de);
            wg_commit();
            if (n == 6) break;
            wg_wait<1>();
            tma3d_if(smb + sf * 16, mw, sq & 15, fb * 64 + (wg ? 0 : 160), smb + O_FULL + (it + 4 + wg) * 8, n == 5 ? 1 : w, 0);
            if (((wg ? 0x1eu : 0x3eu) >> n) & 1) { get(n); put(n); lbar += 8; po += (int)(((pc >> 2) & 63) * (SROWS * 16) + (pc & 3) * 8 - (32 * SROWS * 16 + 8)); pc >>= 8; }
            if (n == 5) {
                const uint32_t m = __ballot_sync(0xffffffffu, (int)(fv - need) < 0);
                asm volatile("{ .reg .pred p, q; elect.sync _|q, 0xffffffff; setp.eq.and.u32 p, %7, 0, q;\n"
                    "@p mbarrier.arrive.expect_tx.shared::cta.b64 _, [%2], 10240;\n"
                    "@p cp.async.bulk.tensor.3d.shared::cluster.global.mbarrier::complete_tx::bytes [%0], [%1, {%5, %4, %3}], [%2];\n"
                    "@p mbarrier.arrive.shared::cta.b64 _, [%6]; }"
                    :: "r"(wr), "l"(&maps.m[11]), "r"(xbar), "r"(((blk & 6) + fpar) * 4), "r"(grow), "r"((blk & 1) * 64), "r"(sbar), "r"(m) : "memory");
                iss = m ? 0 : 0xfff;
            }
            PT3(15 + n);
            wait_item(c, it + 2);
            wg_wait<0>(); pin<0, 32>(acc);
            PT3(24 + n);
            if (r) {
                #pragma unroll
                for (int i = 0; i < 16; i++) asm volatile("cvt.rn.bf16x2.f32 %0, %1, %2;" : "=r"(pk[i ^ 8]) : "f"(acc[2 * i + 1]), "f"(acc[2 * i]));
            } else {
                #pragma unroll
                for (int i = 0; i < 16; i++) pk[i ^ 8] = pack2(acc[2 * (i ^ 8)], acc[2 * (i ^ 8) + 1]);
            }
            if (n == 5) {
                raddr += 1024 + 1024 * r; rbar += xbar - (smb + O_FULL + wg * 40 + 40);
                st_async4(raddr, pk[0], pk[1], pk[2], pk[3], rbar); st_async4(raddr + 512, pk[4], pk[5], pk[6], pk[7], rbar);
                raddr += 1024 - 2048 * r;
            }
            st_async4(raddr, pk[8], pk[9], pk[10], pk[11], rbar); st_async4(raddr + 512, pk[12], pk[13], pk[14], pk[15], rbar);
            raddr += 1024 - (n & 1) * 2048; rbar += 8;
            PT3(7 + n);
        }
        PT(30);
    } else {
        const uint32_t g = lane >> 2, q = lane & 3;
        const uint32_t xh = smb + XR + wg * XH;
        if (q == 0) {
            asm volatile("st.shared.f32 [%0], %1;" :: "r"(smb + O_RSTD + (wg * 64 + w * 16 + g) * 4), "f"(rs_lo) : "memory");
            asm volatile("st.shared.f32 [%0], %1;" :: "r"(smb + O_RSTD + (wg * 64 + w * 16 + g + 8) * 4), "f"(rs_hi) : "memory");
        }
        float M[32], Sx[32], O[16];
        uint32_t pa[16], qf[8], h3[2];
        AttC a;
        a.w = w; a.c0 = 2 * q <= g; a.c1 = 2 * q + 1 <= g;
        a.mcur = (a.c0 ? 0xffffu : 0u) | (a.c1 ? 0xffff0000u : 0u);
        const float SC = 0.18898223650461362f * 1.4426950408889634f;
        a.rq[0] = rs_lo * SC; a.rq[1] = rs_hi * SC;
        const bool qlow = q < 2;
        #pragma unroll
        for (int i = 0; i < 16; i++) pa[i] = 0;
        const uint32_t kst = xh + (lane >> 4) * 1024 + w * 256 + (lane & 15) * 16;
        const uint32_t dk = ((xh & 0x3FFFF) >> 4) | (64u << 16);
        const uint32_t dv = (((xh + 14336) & 0x3FFFF) >> 4) | (8u << 16);
        const uint32_t oo = 28672, qo = oo + (r ? 0 : 14336);
        fv = 0;
        const int row0 = (T0 >> 1) + w * 16;
        auto e_flag = [&]() {
            uint32_t l; asm volatile("mov.u32 %0, %laneid;" : "=r"(l));
            const uint32_t row = min(max((T0 >> 1) + (int)min((l & 30) * 8, 63u), 0), 1023);
            return flags + (64 + (row >> 6) * 2 + (l & 1)) * FST + wg * 4 + ((row >> 4) & 3);
        };
        const uint32_t ibar = lbar0;
        auto e_copy = [&](uint32_t mat, uint32_t off) {
            bulk_ld(xh + off + ((r ? 0 : 10) + w) * 1024, part + G_E + ((mat * 2 + wg) * 8 + 4 * r + w) * SROWS + (T0 >> 1) + 8, 1024, ibar);
        };
        #pragma unroll 1
        for (uint32_t j = 0; ; j++) {
            const uint32_t it = 6 * j;
            const uint32_t p0 = wrap14(r ? 20 - 8 * j : (j == 2 ? 2 : 8 * j));
            const uint32_t gp = ((j + r) & 1) * 7, gq = 7 - gp;
            const uint32_t go = kst + oo + (r ? 28 - 7 * j : 7 * j - 7) * 1024;
            wait_item(c, it); turn_wait(c); wg_fence();
            if (j > 0) { mma_s(Sx, qf, dk + (gq + 3) * 64); mma_pv(O, pa, dv + gq * 64); }
            block448_tail<64>(c, M, xa, it, dring + (it & 3) * SL16);
            wg_wait<1>(); release<0>(c, it);
            if (j > 0) {
                pin<0, 32>(Sx); pin<0, 16>(O);
                softmax_head(Sx, pa, a);
                store_oa(O, go, h3);
                if (j == 2) fv = ld_flag(e_flag());
            } else {
                int klo0 = (int)(w * 16 + 2 * q) - (a.c0 ? 0 : 8), klo1 = (int)(w * 16 + 2 * q + 1) - (a.c1 ? 0 : 8);
                int kk[4] = {klo0, klo1, klo0 + 8, klo1 + 8};
                #pragma unroll
                for (int i = 0; i < 4; i++) {
                    float v;
                    asm volatile("ld.shared.f32 %0, [%1];" : "=f"(v) : "r"(smb + O_RSTD + (wg * 64 + max(kk[i], 0)) * 4) : "memory");
                    a.rk[i] = (T0 < 0 && kk[i] < 7) ? -1e30f : v * a.rq[i >> 1];
                }
            }
            wg_wait<0>(); release<1>(c, it + 1); pin<0, 32>(M);
            stage(M, kst + qo, p0);
            wait_item(c, it + 2); turn_wait(c); wg_fence();
            if (j > 0) mma_pv(O, pa, dv + (gq + 3) * 64);
            block448_tail<64>(c, M, xa, it + 2, dring + ((it + 2) & 3) * SL16);
            wg_wait<1>(); release<2>(c, it + 2);
            load_qa(qf, kst + qo + gp * 1024, qlow);
            if (j > 0) { pin<0, 16>(O); store_ob(O, go, h3, qlow); }
            if (j == 2) {
                PT(33);
                uint32_t base;
                asm volatile("ld.shared.u32 %0, [%1];" : "=r"(base) : "r"(smb + O_EPOCH) : "memory");
                if (warp == 7 && elect_one()) {
                    #pragma unroll
                    for (int j = 0; j < 12; j++) if ((PB >> j) & 1) asm volatile("prefetch.tensormap [%0];" :: "l"(&maps.m[j]) : "memory");
                }
                gate(e_flag(), fv, base + 1, true);
                if (elect_one()) { e_copy(0, qo); e_copy(1, 0); e_copy(2, 14336); }
                PT(34);
            }
            wg_wait<0>(); release<3>(c, it + 3); pin<0, 32>(M);
            stage(M, kst, p0);
            fence_async();
            if (j == 2) break;
            wait_item(c, it + 4); turn_wait(c); wg_fence();
            mma_s(Sx, qf, dk + gp * 64);
            block448_tail<64>(c, M, xa, it + 4, dring + (it & 3) * SL16);
            wg_wait<1>(); release<2>(c, it + 4);
            pin<0, 32>(Sx);
            softmax_head(Sx, pa, a);
            load_qb(qf, kst + qo + gp * 1024, qlow);
            wg_wait<0>(); release<3>(c, it + 5); pin<0, 32>(M);
            stage(M, kst + 14336, p0);
            fence_async();
            PT(2 + j);
        }
        float O2[16], A1[64], A2[64], v[4][4];
        uint32_t pb[16], qg[8], oa[56], x[4][4];
        const uint32_t gp = r ? 0 : 7, gq = 7 - gp;
        const uint32_t g2 = kst + oo + (r ? 7 : 14) * 1024, g3 = kst + oo + (r ? 0 : 21) * 1024;
        const uint32_t doe = dk + (oo >> 4) + gq * 128, dw = dring | (896u << 16);
        uint64_t dd = mkdesc(dring, DH_W);
        load_qb(qg, kst + qo + gq * 1024, qlow);
        mbar_wait(ibar, 0);
        wait_item(c, 16); turn_wait(c); wg_fence();
        PT(35);
        mma_s(Sx, qf, dk + gq * 64); wg_commit();
        mma_w<64, 0, 7, 0, 1>(M, xa, dd); wg_commit();
        wg_wait<1>(); pin<0, 32>(Sx); pick_w(Sx, v[0], a); wg_fence();
        mma_s(Sx, qg, dk + (gq + 3) * 64); wg_commit();
        load_qa(qf, kst + qo + gp * 1024, qlow);
        mma_w<64, 0, 7, 7, 0>(M, xa, dd); wg_commit();
        wait_item(c, 17);
        wg_wait<1>(); pin<0, 32>(Sx); pick_w(Sx, v[1], a); wg_fence();
        mma_s(Sx, qf, dk + gp * 64); wg_commit();
        load_qb(qg, kst + qo + gp * 1024, qlow);
        mma_w<64, 0, 7, 14, 0>(M, xa, dd); wg_commit();
        wg_wait<1>(); pin<0, 32>(Sx); pick_w(Sx, v[2], a); wg_fence();
        mma_s(Sx, qg, dk + (gp + 3) * 64); wg_commit();
        mma_w<64, 0, 7, 21, 0>(M, xa, dd); wg_commit();
        turn_pass(c);
        PT(36);
        wg_wait<1>(); pin<0, 32>(Sx); pick_w(Sx, v[3], a);
        soft1<4>(v, a);
        wg_wait<0>(); pin<0, 32>(M);
        stage(M, kst + 14336, r ? 4 : 2);
        fence_async();
        PT(4);
        float sv[4][2];
        uint32_t ko[14];
        soft2<4>(v, sv);
        soft3(v[0], sv[0], x[0], a); soft3(v[1], sv[1], x[1], a);
        #pragma unroll
        for (int i = 0; i < 8; i++) asm volatile("" : "+r"(x[i >> 2][i & 3]) :: "memory");
        PT(5);
        wait_item(c, 18);
        asm volatile("{ .reg .pred p; setp.eq.u32 p, %0, 0; @p bar.sync 1, 256; }" :: "r"(wg) : "memory");
        wg_fence();
        mma_early(A1, doe, dw + 2 * SL16);
        wg_commit();
        PT(26);
        #pragma unroll
        for (int i = 0; i < 16; i++) pb[i] = 0;
        place2(pa, pb, x[0], x[1], a);
        PT(27);
        wait_item(c, 19);
        asm volatile("{ .reg .pred p; setp.ne.u32 p, %0, 0; @p bar.sync 2, 256; }" :: "r"(wg) : "memory");
        wg_fence();
        PT(24);
        mma_pv(O, pa, dv + gq * 64); mma_pv(O2, pb, dv + (gq + 3) * 64);
        wg_commit();
        mma_early(A2, doe, dw + 3 * SL16);
        wg_commit();
        soft3(v[2], sv[2], x[2], a); soft3(v[3], sv[3], x[3], a);
        #pragma unroll
        for (int i = 8; i < 16; i++) asm volatile("" : "+r"(x[i >> 2][i & 3]) :: "memory");
        wg_wait<1>(); pin<0, 16>(O); pin<0, 16>(O2); pin<0, 64>(A1);
        tma3d_if(smb + w * SLOT, &maps.m[7], wg ? 2 : 4 * w, wg ? 336 * r : 112 + 112 * r, smb + O_FULL + (20 + w) * 8, (0x43u >> warp) & 1, 1);
        place2(pa, pb, x[2], x[3], a);
        pack_o(ko, O, O2, qlow);
        wg_fence();
        mma_pv(O, pa, dv + gp * 64); mma_pv(O2, pb, dv + (gp + 3) * 64);
        wg_commit();
        turn_pass(c);
        PT(25);
        store_o(ko, g2);
        wg_wait<0>(); pin<0, 16>(O); pin<0, 16>(O2); pin<0, 64>(A2);
        pack_o(ko, O, O2, qlow);
        store_o(ko, g3);
        __syncwarp();
        #pragma unroll
        for (int k = 0; k < 7; k++) ldsm4(oa[28 + 4 * k], oa[29 + 4 * k], oa[30 + 4 * k], oa[31 + 4 * k], kst + oo + (gp + k) * 2048);
        #pragma unroll
        for (int k = 0; k < 7; k++) ldsm4(oa[4 * k], oa[4 * k + 1], oa[4 * k + 2], oa[4 * k + 3], kst + oo + (gq + k) * 2048);
        uint32_t base;
        asm volatile("ld.shared.u32 %0, [%1];" : "=r"(base) : "r"(smb + O_EPOCH) : "memory");
        const uint32_t tx = ((lane >> 4) ^ ((row0 + lane) & 7)) * 16, tw = wr + (lane & 15) * 256 + tx;
        par = (base >> 3) & 1;
        const uint32_t sk = w ? 0 : 7, sr = (wg * 4 + 2 + r) * SROWS + row0 + sk;
        auto send = [&](uint32_t off, uint32_t idx) {
            fence_async();
            __syncwarp();
            if (elect_one()) bulk_st(part + G_S + (idx * 8 * SROWS + sr) * 16, wr + off + sk * 256, (16 - sk) * 256);
            bulk_commit();
        };
        PT(6);
        wait_item(c, 20); wait_item(c, 21); turn_wait(c); wg_fence();
        dd = mkdesc(dw, DH_W); mma_w<128, 0, 7, 7, 0>(A1, oa, dd);
        wg_commit();
        dd = mkdesc(dw + SL16, DH_W); mma_w<128, 0, 7, 7, 0>(A2, oa, dd);
        wg_commit();
        turn_pass(c);
        PT(28);
        wg_wait<1>(); pin<0, 64>(A1);
        tma3d_if(smb + (wg ? 0 : 3 * SLOT), &maps.m[wg ? 2 : 7], wg ? 6 : 2, wg ? 224 * r : 112 + 112 * r, smb + O_FULL + (23 + wg) * 8, w, 3);
        PT(29);
        stage_rows<0, true>(tw, 0, A1, par); stage_rows<32, true>(tw, 128, A1, par); PT(30); send(0, 0);
        PT(31);
        wg_wait<0>(); pin<0, 64>(A2);
        PT(32);
        stage_rows<0, true>(tw, 4096, A2, par); stage_rows<32, true>(tw, 4096 + 128, A2, par); send(4096, 2);
        PT(7);
        wait_item(c, 22); wait_item(c, 23); turn_wait(c); wg_fence();
        dd = mkdesc(dw + 2 * SL16, DH_W); mma_w<128, 0, 7, 0, 1>(A1, oa, dd);
        dd = mkdesc(dw + 3 * SL16, DH_W); mma_w<128, 0, 7, 7, 0>(A1, oa, dd);
        wg_commit();
        turn_pass(c);
        publish<0>(fl, base + 1, lane);
        PT(10);
        wg_wait<0>(); pin<0, 64>(A1);
        stage_rows<0, true>(tw, 8192, A1, par); stage_rows<32, true>(tw, 8192 + 128, A1, par); send(8192, 1);
        PT(11);
        wait_item(c, 24); turn_wait(c); wg_fence();
        dd = mkdesc(dring + gq * 128, DH_W); mma_w<64, 0, 7, 0, 1>(A2, oa, dd);
        dd = mkdesc(dring + gp * 128, DH_W); mma_w<64, 0, 7, 7, 0>(A2, oa, dd);
        wg_commit();
        if (wg == 0) turn_pass(c);
        publish<0>(fl, base + 2, lane);
        PT(12);
        wg_wait<0>(); pin<0, 32>(A2);
        stage_rows<0, true>(tw - (lane & 15) * 128, 0, A2, par);
        __syncwarp();
        #pragma unroll
        for (int t = 0; t < 4; t++) {
            uint4 z;
            lds128(z.x, z.y, z.z, z.w, wr + lane * 16 + t * 512);
            if (4 * t + (lane >> 3) >= sk) part[G_S + (24 * SROWS + sr - sk + 4 * t + (lane >> 3)) * 16 + (lane & 7)] = z;
        }
        PT(8);
        publish<0>(fl, base + 3, lane);
        PT(9);
        if (wg == 1 || pair >= 64) { GT(47); PDUMP(); return; }
        blk = FB; grow = (pair - 48) * 64 + w * 16; fpar = r;
        if (elect_one()) { mbar_expect_tx(xbar, 2048); tma4d(wr + 5 * 2048, &maps.m[8], grow, FB, fpar, xbar); }
        final_deps(lane, lane & 1, base + 3, base + 6, base + 6);
        fv = ld_flag(fp);
        mbar_wait(xbar, 1); xph = 0;
        final_x(lane, 5 * 2048);
        #pragma unroll
        for (int i = 0; i < 32; i++) asm volatile("mov.b32 %0, 0f00000000;" : "=f"(acc[i]));
    }
    uint32_t o[16];
    #pragma unroll 1
    for (uint32_t k = 0; ; k++, xph ^= 1) {
        uint32_t bad = 0, a[16], b[16], d[16];
        const uint32_t bk = blk + (k >> 8);
        if (iss != 0xfff) {
            PT4(13);
            ainit();
            #pragma unroll 1
            for (int j = 0; ; j++) {
                apoll();
                const uint32_t m = j < SPIN_MAX ? __ballot_sync(0xffffffffu, (int)(fv - need) < 0) : 0;
                part1_if(wr + 6 * 2048, &maps.m[10], 24 + fpar * 4, grow, xbar, ((m | iss) & 0xfc0) | (bk ^ FB));
                final_loads(bk, m, k && bk != FB ? 4096 : 6144);
                if (iss == 0xfff) break;
                __nanosleep(NAP);
                aread();
            }
            PT4(15);
        }
        PT(31);
        mbar_wait(xbar, xph);
        PT(37);
        #pragma unroll
        for (int t = 0; t < 4; t++) {
            lds128(a[4 * t], a[4 * t + 1], a[4 * t + 2], a[4 * t + 3], pq + t * 512);
            lds128(b[4 * t], b[4 * t + 1], b[4 * t + 2], b[4 * t + 3], pq + 2048 + t * 512);
            lds128(d[4 * t], d[4 * t + 1], d[4 * t + 2], d[4 * t + 3], pq + 6 * 2048 + t * 512);
        }
        iss = 0;
        uint32_t es, sa[16], sb[16], z[16];
        auto early_s = [&]() {
            asm volatile("{ .reg .pred p; mbarrier.test_wait.parity.shared::cta.b64 p, [%1], %2; selp.u32 %0, 1, 0, p; }" : "=r"(es) : "r"(sbar), "r"(~k & 1) : "memory");
            #pragma unroll
            for (int t = 0; t < 4; t++)
                asm volatile("{ .reg .pred p; setp.ne.u32 p, %9, 0; @p ld.shared.v4.u32 {%0,%1,%2,%3}, [%8 + 4096]; @p ld.shared.v4.u32 {%4,%5,%6,%7}, [%8 + 6144]; }"
                    : "=r"(sa[4 * t]), "=r"(sa[4 * t + 1]), "=r"(sa[4 * t + 2]), "=r"(sa[4 * t + 3]), "=r"(sb[4 * t]), "=r"(sb[4 * t + 1]), "=r"(sb[4 * t + 2]), "=r"(sb[4 * t + 3])
                    : "r"((oq ^ ((t & 1) * 64)) + t * 512), "r"(es) : "memory");
        };
        wg_wait<0>(); pin<0, 32>(acc);
        PT(32);
        #pragma unroll
        for (int t = 0; t < 4; t++) chk(bad, d[4 * t], par);
        bad &= bk == FB;
        #pragma unroll
        for (int t = 0; t < 4; t++) {
            if (t == EM) early_s();
            chk(bad, a[4 * t], par); chk(bad, b[4 * t], par);
            #pragma unroll
            for (int i = 4 * t; i < 4 * t + 4; i++) {
                const uint32_t v = hadd2(hadd2(a[i], b[i]), d[i]);
                const uint32_t y = i < ZG * ZL ? 0 : z[i / ZG - ZL];
                const float e = acc[2 * i] + __uint_as_float(__byte_perm(v, y, 0x1044)), f = acc[2 * i + 1] + __uint_as_float(__byte_perm(v, y, 0x3244));
                const float te = tanh_fast(e);
                if (i % ZG == 0) z[i / ZG] = __float_as_uint(te) & (pq & 15);
                a[i] = pack2(fmaf(e, te, e), fmaf(f, tanh_fast(f), f));
            }
            stsm4(tq[t] + 5 * 2048, a[4 * t], a[4 * t + 1], a[4 * t + 2], a[4 * t + 3]);
        }
        PT(33);
        #pragma unroll 1
        for (;; k++) {
            if (!__all_sync(0xffffffffu, es)) {
                mbar_wait(sbar, ~k & 1);
                #pragma unroll
                for (int t = 0; t < 4; t++) {
                    const uint32_t q = (oq ^ ((t & 1) * 64)) + t * 512;
                    lds128(sa[4 * t], sa[4 * t + 1], sa[4 * t + 2], sa[4 * t + 3], q + 2 * 2048);
                    lds128(sb[4 * t], sb[4 * t + 1], sb[4 * t + 2], sb[4 * t + 3], q + 3 * 2048);
                }
            }
            es = 0;
            __syncwarp();
            PT(36);
            uint32_t bs = 0;
            #pragma unroll
            for (int t = 0; t < 4; t++) {
                lds128(d[4 * t], d[4 * t + 1], d[4 * t + 2], d[4 * t + 3], (oq ^ ((t & 1) * 64)) + t * 512 + 5 * 2048);
                chk(bs, sa[4 * t], par); chk(bs, sb[4 * t], par);
            }
            #pragma unroll
            for (int i = 0; i < 16; i++) o[i] = hfma2(hadd2(sa[i], sb[i]), d[i], xv[i]);
            PT(34);
            if (!__any_sync(0xffffffffu, (bad | ((pq & 0x70) ? 0 : bs)) & 1) || k >= 64) goto done;
            if (__any_sync(0xffffffffu, bad & 1)) { RT(3); break; }
            RT(2);
            const uint32_t b2 = blk + (k >> 8);
            part_if(wr + 4096, &maps.m[9], ((b2 & 6) + fpar) * 4 + 2, grow, (b2 & 1) * 64, sbar, 4096, 0);
        }
    }
done:
    #pragma unroll
    for (int t = 0; t < 4; t++) asm volatile("st.global.v4.u32 [%0], {%1,%2,%3,%4};" :: "l"(op + t * 8 * 56), "r"(o[4 * t]), "r"(o[4 * t + 1]), "r"(o[4 * t + 2]), "r"(o[4 * t + 3]) : "memory");
    asm volatile("cp.async.wait_all;" ::: "memory");
    PT(35);
    GT(47); PDUMP();
}

typedef CUresult (*EncodeFn)(CUtensorMap*, CUtensorMapDataType, cuuint32_t, void*, const cuuint64_t*, const cuuint64_t*, const cuuint32_t*,
                             const cuuint32_t*, CUtensorMapInterleave, CUtensorMapSwizzle, CUtensorMapL2promotion, CUtensorMapFloatOOBfill);

void enc3d(EncodeFn f, CUtensorMap* m, void* ptr, uint64_t cols, uint64_t rows, uint32_t box_r, uint32_t box_b) {
    cuuint64_t dims[3] = {64, rows, cols / 64}; cuuint64_t str[2] = {cols * 2, 128}; cuuint32_t box[3] = {64, box_r, box_b}; cuuint32_t es[3] = {1, 1, 1};
    f(m, CU_TENSOR_MAP_DATA_TYPE_BFLOAT16, 3, ptr, dims, str, box, es, CU_TENSOR_MAP_INTERLEAVE_NONE, CU_TENSOR_MAP_SWIZZLE_128B,
      CU_TENSOR_MAP_L2_PROMOTION_NONE, CU_TENSOR_MAP_FLOAT_OOB_FILL_NONE);
}

}

extern "C" void kernel_launch(void* const* d_in, const int* in_sizes, int n_in, void* d_out, int out_size) {
    (void)in_sizes; (void)n_in; (void)out_size;
    static EncodeFn enc = nullptr;
    static void* part = nullptr;
    if (!enc) {
        void* fn = nullptr; cudaDriverEntryPointQueryResult qr;
        cudaGetDriverEntryPoint("cuTensorMapEncodeTiled", &fn, cudaEnableDefault, &qr);
        enc = (EncodeFn)fn;
        cudaGetSymbolAddress(&part, g_part);
        cudaFuncSetAttribute(fused_kernel, cudaFuncAttributeMaxDynamicSharedMemorySize, SMEM_BYTES);
    }
    Maps maps;
    for (int i = 0; i < 2; i++) {
        cuuint64_t dims[4] = {64, 1024, 7, 2}; cuuint64_t str[3] = {1792, 128, 896}; cuuint32_t box[4] = {64, 16, i ? 1u : 7u, 1}; cuuint32_t es[4] = {1, 1, 1, 1};
        enc(&maps.m[8 * i], CU_TENSOR_MAP_DATA_TYPE_BFLOAT16, 4, d_in[0], dims, str, box, es, CU_TENSOR_MAP_INTERLEAVE_NONE, CU_TENSOR_MAP_SWIZZLE_128B,
            CU_TENSOR_MAP_L2_PROMOTION_L2_128B, CU_TENSOR_MAP_FLOAT_OOB_FILL_NONE);
    }
    enc3d(enc, &maps.m[1], d_in[1], 1344, 448, 224, 1);
    enc3d(enc, &maps.m[2], d_in[2], 448, 448, 224, 1);
    enc3d(enc, &maps.m[3], d_in[4], 1792, 448, 224, 1);
    enc3d(enc, &maps.m[4], d_in[5], 1792, 448, 224, 1);
    enc3d(enc, &maps.m[5], d_in[6], 448, 1792, 160, 1);
    enc3d(enc, &maps.m[6], d_in[6], 448, 1792, 96, 1);
    enc3d(enc, &maps.m[7], d_in[2], 448, 448, 112, 2);
    for (int i = 0; i < 3; i++) {
        cuuint64_t dims[3] = {128, SROWS, 32}; cuuint64_t str[2] = {256, 256 * SROWS}; cuuint32_t box[3] = {64, 16, i == 2 ? 4u : 2u - i}; cuuint32_t es[3] = {1, 1, 1};
        enc(&maps.m[9 + i], CU_TENSOR_MAP_DATA_TYPE_BFLOAT16, 3, (uint4*)part + G_S, dims, str, box, es, CU_TENSOR_MAP_INTERLEAVE_NONE,
            CU_TENSOR_MAP_SWIZZLE_NONE, CU_TENSOR_MAP_L2_PROMOTION_NONE, CU_TENSOR_MAP_FLOAT_OOB_FILL_NONE);
    }
    fused_kernel<<<132, 256, SMEM_BYTES, cudaStreamPerThread>>>(maps, (const char*)d_in[0], (uint4*)d_out, (uint4*)part);
}
```
